```python
import torch

def _softmax(x, axis=-1):
    return torch.softmax(x, dim=axis)

def _gelu(x):
    return torch.nn.functional.gelu(x, approximate='tanh')

def _silu(x):
    return torch.nn.functional.silu(x)

def _sigmoid(x):
    return torch.sigmoid(x)

def _layernorm(x, axis=-1, eps=1e-05):
    m = x.mean(dim=axis, keepdim=True)
    v = x.var(dim=axis, keepdim=True, unbiased=False)
    return (x - m) / torch.sqrt(v + eps)

def _scatter_add(tgt, idx, src, axis=0):
    return tgt.clone().index_add_(axis, idx, src)

def _segment_sum(src, seg, n):
    out = torch.zeros((n,) + src.shape[1:], dtype=src.dtype)
    return out.index_add_(0, seg, src)

def _pad(x, pw):
    flat = tuple((v for pair in reversed(pw) for v in pair))
    return torch.nn.functional.pad(x, flat)
kernel_name = 'adaLN_cond__spectral_gfnet__mixer_token_mlp__prompt'

def setup_inputs():

    _w = lambda a: (lambda t: t.to(torch.bfloat16) if t.is_floating_point() else t)(torch.as_tensor(a))

    def _A_setup():
        B, S, D = (1, 2048, 640)
        Df = D // 2 + 1
        return {'x': _w((lambda *s: torch.randn(*s, dtype=torch.bfloat16) * 0.05)(B, S, D)), 'w_r': _w((lambda *s: torch.randn(*s, dtype=torch.bfloat16) * 1.6)(S, Df) * 0.02), 'w_i': _w((lambda *s: torch.randn(*s, dtype=torch.bfloat16) * 1.6)(S, Df) * 0.02)}
    _A_in = _A_setup()

    def _B_setup():
        B, S, D, F = (1, 2048, 640, 1728)
        return {'x': _w((lambda *s: torch.randn(*s, dtype=torch.bfloat16) * 0.05)(B, S, D)), 'w1': _w((lambda *s: torch.randn(*s, dtype=torch.bfloat16) * 0.8)(S, F) * S ** (-0.5)), 'b1': _w((lambda *s: torch.randn(*s, dtype=torch.bfloat16) * 6.4)(F) * 0.02), 'w2': _w((lambda *s: torch.randn(*s, dtype=torch.bfloat16) * 0.1)(F, S) * F ** (-0.5)), 'b2': _w((lambda *s: torch.randn(*s, dtype=torch.bfloat16) * 0.8)(S) * 0.02)}
    _B_in = _B_setup()
    return {'A_x': _A_in['x'], 'A_w_r': _A_in['w_r'], 'A_w_i': _A_in['w_i'], 'B_x': _B_in['x'], 'B_w1': _B_in['w1'], 'B_b1': _B_in['b1'], 'B_w2': _B_in['w2'], 'B_b2': _B_in['b2'], 'c': _w((lambda *s: torch.randn(*s, dtype=torch.bfloat16) * 0.1)(1, 640) * 8.0), 'w_mod': _w((lambda *s: torch.randn(*s, dtype=torch.bfloat16) * 0.1)(640, 6 * 640) * 640 ** (-0.5) * 8.0)}

def reference(A_x, A_w_r, A_w_i, B_x, B_w1, B_b1, B_w2, B_b2, c, w_mod):

    def _A_ref(x, w_r, w_i):
        B, S, D = x.shape
        X = (lambda x, axes=(-2, -1): torch.fft.rfft2(x.float(), dim=axes))(x, axes=(-2, -1))
        W = w_r + 1j * w_i
        X = X * W
        y = (lambda x, s, axes=(-2, -1): torch.fft.irfft2(x, s=s, dim=axes).to(torch.bfloat16))(X, (S, D), axes=(-2, -1))
        return y

    def _B_ref(x, w1, b1, w2, b2):
        B, S, D = x.shape
        h = _layernorm(x, axis=-1)
        u = torch.einsum('bsd,sf->bdf', h, w1) + b1
        u = _gelu(u)
        y = torch.einsum('bdf,fs->bds', u, w2) + b2
        return (lambda x, *d: x.permute(*d))(y, 0, 2, 1)
    x = A_x
    mod = (_silu(c) @ w_mod).reshape(c.shape[0], 6, 1, -1)
    sa, ca, ga, sb, cb, gb = (mod[:, 0].clone(), mod[:, 1].clone(), mod[:, 2].clone(), mod[:, 3].clone(), mod[:, 4].clone(), mod[:, 5].clone())
    h = _layernorm(x, axis=-1) * (1 + ca) + sa
    x = x + ga * _A_ref(h, A_w_r, A_w_i)
    h = _layernorm(x, axis=-1) * (1 + cb) + sb
    x = x + gb * _B_ref(h, B_w1, B_b1, B_w2, B_b2)
    return x
```

```cpp
#include <cuda_runtime.h>
#include <cuda_bf16.h>
#include <cuda.h>
#include <stdint.h>

typedef __nv_bfloat16 bf16;
#define CK(kid, ev) do {} while (0)
#define TL(kid, ev) do {} while (0)

__device__ __forceinline__ uint32_t smem_u32(const void* p) { return (uint32_t)__cvta_generic_to_shared(p); }
__device__ __forceinline__ void mbar_init(uint32_t bar, uint32_t cnt) { asm volatile("mbarrier.init.shared::cta.b64 [%0], %1;" ::"r"(bar), "r"(cnt) : "memory"); }
__device__ __forceinline__ void mbar_expect_tx(uint32_t bar, uint32_t bytes) { asm volatile("mbarrier.arrive.expect_tx.shared::cta.b64 _, [%0], %1;" ::"r"(bar), "r"(bytes) : "memory"); }
__device__ __forceinline__ void mbar_arrive(uint32_t bar) { asm volatile("mbarrier.arrive.shared::cta.b64 _, [%0];" ::"r"(bar) : "memory"); }
__device__ __forceinline__ void mbar_arrive_cluster(uint32_t bar_cluster_addr) { asm volatile("mbarrier.arrive.shared::cluster.b64 _, [%0];" ::"r"(bar_cluster_addr) : "memory"); }
__device__ __forceinline__ bool mbar_try_wait(uint32_t bar, uint32_t parity) {
  uint32_t ok;
  asm volatile("{\n.reg .pred p;\nmbarrier.try_wait.parity.shared::cta.b64 p, [%1], %2;\nselp.u32 %0, 1, 0, p;\n}\n" : "=r"(ok) : "r"(bar), "r"(parity) : "memory");
  return ok;
}
__device__ __forceinline__ void mbar_wait(uint32_t bar, uint32_t parity) {
  asm volatile("{\n.reg .pred p, q;\n.reg .u32 n;\nmov.u32 n, 0;\n"
               "LW:\nmbarrier.try_wait.parity.shared::cta.b64 p, [%0], %1;\n@p bra.uni LD;\n"
               "add.u32 n, n, 1;\nsetp.lt.u32 q, n, 16777216;\n@q bra.uni LW;\ntrap;\nLD:\n}\n" ::"r"(bar), "r"(parity) : "memory");
}
__device__ __forceinline__ bool mbar_try_wait_cluster(uint32_t bar, uint32_t parity) {
  uint32_t ok;
  asm volatile("{\n.reg .pred p;\nmbarrier.try_wait.parity.acquire.cluster.shared::cta.b64 p, [%1], %2;\nselp.u32 %0, 1, 0, p;\n}\n" : "=r"(ok) : "r"(bar), "r"(parity) : "memory");
  return ok;
}
__device__ __forceinline__ void mbar_wait_cluster(uint32_t bar, uint32_t parity) {
  asm volatile("{\n.reg .pred p, q;\n.reg .u32 n;\nmov.u32 n, 0;\n"
               "LW:\nmbarrier.try_wait.parity.acquire.cluster.shared::cta.b64 p, [%0], %1;\n@p bra.uni LD;\n"
               "add.u32 n, n, 1;\nsetp.lt.u32 q, n, 16777216;\n@q bra.uni LW;\ntrap;\nLD:\n}\n" ::"r"(bar), "r"(parity) : "memory");
}
__device__ __forceinline__ void fence_mbar_init() { asm volatile("fence.mbarrier_init.release.cluster;" ::: "memory"); }
__device__ __forceinline__ void fence_proxy_async() { asm volatile("fence.proxy.async.shared::cta;" ::: "memory"); }
__device__ __forceinline__ void cluster_arrive() { asm volatile("barrier.cluster.arrive.release.aligned;" ::: "memory"); }
__device__ __forceinline__ void cluster_arrive_relaxed() { asm volatile("barrier.cluster.arrive.relaxed.aligned;" ::: "memory"); }
__device__ __forceinline__ void cluster_wait() { asm volatile("barrier.cluster.wait.acquire.aligned;" ::: "memory"); }
__device__ __forceinline__ uint32_t cluster_rank() { uint32_t r; asm volatile("mov.u32 %0, %%cluster_ctarank;" : "=r"(r)); return r; }
__device__ __forceinline__ uint32_t mapa(uint32_t addr, uint32_t rank) { uint32_t r; asm volatile("mapa.shared::cluster.u32 %0, %1, %2;" : "=r"(r) : "r"(addr), "r"(rank)); return r; }
__device__ __forceinline__ void pdl_wait() { asm volatile("griddepcontrol.wait;" ::: "memory"); }
__device__ __forceinline__ void pdl_trigger() { asm volatile("griddepcontrol.launch_dependents;" ::: "memory"); }

__device__ __forceinline__ void tma_load_2d(uint32_t dst, const CUtensorMap* tm, int c0, int c1, uint32_t bar) {
  asm volatile("cp.async.bulk.tensor.2d.shared::cluster.global.mbarrier::complete_tx::bytes [%0], [%1, {%3, %4}], [%2];"
    ::"r"(dst), "l"(tm), "r"(bar), "r"(c0), "r"(c1) : "memory");
}
__device__ __forceinline__ void tma_load_2d_mc(uint32_t dst, const CUtensorMap* tm, int c0, int c1, uint32_t bar, uint16_t mask) {
  asm volatile("cp.async.bulk.tensor.2d.shared::cluster.global.mbarrier::complete_tx::bytes.multicast::cluster [%0], [%1, {%3, %4}], [%2], %5;"
    ::"r"(dst), "l"(tm), "r"(bar), "r"(c0), "r"(c1), "h"(mask) : "memory");
}
__device__ __forceinline__ void tma_load_3d(uint32_t dst, const CUtensorMap* tm, int c0, int c1, int c2, uint32_t bar) {
  asm volatile("cp.async.bulk.tensor.3d.shared::cluster.global.mbarrier::complete_tx::bytes [%0], [%1, {%3, %4, %5}], [%2];"
    ::"r"(dst), "l"(tm), "r"(bar), "r"(c0), "r"(c1), "r"(c2) : "memory");
}
__device__ __forceinline__ void tma_prefetch_2d(const CUtensorMap* tm, int c0, int c1) {
  asm volatile("cp.async.bulk.prefetch.tensor.2d.L2.global [%0, {%1, %2}];" ::"l"(tm), "r"(c0), "r"(c1) : "memory");
}
__device__ __forceinline__ void tma_store_2d(const CUtensorMap* tm, uint32_t src, int c0, int c1) {
  asm volatile("cp.async.bulk.tensor.2d.global.shared::cta.bulk_group [%0, {%2, %3}], [%1];"
    ::"l"(tm), "r"(src), "r"(c0), "r"(c1) : "memory");
}
__device__ __forceinline__ void bulk_commit() { asm volatile("cp.async.bulk.commit_group;" ::: "memory"); }
__device__ __forceinline__ void bulk_wait_read0() { asm volatile("cp.async.bulk.wait_group.read 0;" ::: "memory"); }
__device__ __forceinline__ void bulk_wait0() { asm volatile("cp.async.bulk.wait_group 0;" ::: "memory"); }
__device__ __forceinline__ void bulk_load(uint32_t dst, const void* src, uint32_t bytes, uint32_t bar) {
  asm volatile("cp.async.bulk.shared::cluster.global.mbarrier::complete_tx::bytes [%0], [%1], %2, [%3];"
    ::"r"(dst), "l"(src), "r"(bytes), "r"(bar) : "memory");
}
__device__ __forceinline__ void prefetch_tmap(const CUtensorMap* tm) { asm volatile("prefetch.tensormap [%0];" ::"l"(tm) : "memory"); }
__device__ __forceinline__ void prefetch_l2_bulk(const void* p, uint32_t bytes) { asm volatile("cp.async.bulk.prefetch.L2.global [%0], %1;" ::"l"(p), "r"(bytes) : "memory"); }

__device__ __forceinline__ void wgmma_fence() { asm volatile("wgmma.fence.sync.aligned;" ::: "memory"); }
__device__ __forceinline__ void wgmma_commit() { asm volatile("wgmma.commit_group.sync.aligned;" ::: "memory"); }
template<int N> __device__ __forceinline__ void wgmma_wait() { asm volatile("wgmma.wait_group.sync.aligned %0;" ::"n"(N) : "memory"); }
__device__ __forceinline__ uint64_t make_desc_sw128(uint32_t addr, uint32_t lbo_bytes, uint32_t sbo_bytes) {
  return (uint64_t)((addr & 0x3FFFF) >> 4) | ((uint64_t)((lbo_bytes >> 4) & 0x3FFF) << 16) | ((uint64_t)((sbo_bytes >> 4) & 0x3FFF) << 32) | (1ull << 62);
}
template<int N> __device__ __forceinline__ void reg_fence(float (&d)[N]) {
#pragma unroll
  for (int i = 0; i < N; i++) asm volatile("" : "+f"(d[i]) :: "memory");
}
__device__ __forceinline__ void st_async_v4(uint32_t dst_cluster, float a, float b, float c, float d, uint32_t bar_cluster) {
  asm volatile("st.async.weak.shared::cluster.mbarrier::complete_tx::bytes.v4.b32 [%0], {%1, %2, %3, %4}, [%5];"
    ::"r"(dst_cluster), "r"(__float_as_uint(a)), "r"(__float_as_uint(b)), "r"(__float_as_uint(c)), "r"(__float_as_uint(d)), "r"(bar_cluster) : "memory");
}
__device__ __forceinline__ void st_async_b32(uint32_t dst_cluster, uint32_t v, uint32_t bar_cluster) {
  asm volatile("st.async.weak.shared::cluster.mbarrier::complete_tx::bytes.b32 [%0], %1, [%2];" ::"r"(dst_cluster), "r"(v), "r"(bar_cluster) : "memory");
}
__device__ __forceinline__ void stmatrix_x4(uint32_t addr, uint32_t r0, uint32_t r1, uint32_t r2, uint32_t r3) {
  asm volatile("stmatrix.sync.aligned.m8n8.x4.shared.b16 [%0], {%1, %2, %3, %4};" ::"r"(addr), "r"(r0), "r"(r1), "r"(r2), "r"(r3) : "memory");
}
__device__ __forceinline__ void stmatrix_x4_trans(uint32_t addr, uint32_t r0, uint32_t r1, uint32_t r2, uint32_t r3) {
  asm volatile("stmatrix.sync.aligned.m8n8.x4.trans.shared.b16 [%0], {%1, %2, %3, %4};" ::"r"(addr), "r"(r0), "r"(r1), "r"(r2), "r"(r3) : "memory");
}
__device__ __forceinline__ void stmatrix_x2(uint32_t addr, uint32_t r0, uint32_t r1) {
  asm volatile("stmatrix.sync.aligned.m8n8.x2.shared.b16 [%0], {%1, %2};" ::"r"(addr), "r"(r0), "r"(r1) : "memory");
}
__device__ __forceinline__ void ldmatrix_x4(uint32_t (&r)[4], uint32_t addr) {
  asm volatile("ldmatrix.sync.aligned.m8n8.x4.shared.b16 {%0, %1, %2, %3}, [%4];" : "=r"(r[0]), "=r"(r[1]), "=r"(r[2]), "=r"(r[3]) : "r"(addr) : "memory");
}
__device__ __forceinline__ void ldmatrix_x4_trans(uint32_t (&r)[4], uint32_t addr) {
  asm volatile("ldmatrix.sync.aligned.m8n8.x4.trans.shared.b16 {%0, %1, %2, %3}, [%4];" : "=r"(r[0]), "=r"(r[1]), "=r"(r[2]), "=r"(r[3]) : "r"(addr) : "memory");
}
__device__ __forceinline__ void mma16816(float (&d)[4], uint32_t a0, uint32_t a1, uint32_t a2, uint32_t a3, uint32_t b0, uint32_t b1) {
  asm volatile("mma.sync.aligned.m16n8k16.row.col.f32.bf16.bf16.f32 {%0,%1,%2,%3}, {%4,%5,%6,%7}, {%8,%9}, {%0,%1,%2,%3};"
    : "+f"(d[0]), "+f"(d[1]), "+f"(d[2]), "+f"(d[3]) : "r"(a0), "r"(a1), "r"(a2), "r"(a3), "r"(b0), "r"(b1));
}
__device__ __forceinline__ uint32_t pack_bf16(float lo, float hi) {
  uint32_t r; asm("cvt.rn.bf16x2.f32 %0, %1, %2;" : "=r"(r) : "f"(hi), "f"(lo)); return r;
}
__device__ __forceinline__ float bfr(float x) { return __bfloat162float(__float2bfloat16_rn(x)); }
__device__ __forceinline__ float bf_lo(uint32_t v) { return __uint_as_float(v << 16); }
__device__ __forceinline__ float bf_hi(uint32_t v) { return __uint_as_float(v & 0xffff0000u); }
template<int TA, int TB> __device__ __forceinline__ void wgmma_ss_n64(float (&d)[32], uint64_t da, uint64_t db, int sd) {
  asm volatile("{\n.reg .pred p;\nsetp.ne.b32 p, %34, 0;\n"
    "wgmma.mma_async.sync.aligned.m64n64k16.f32.bf16.bf16 {%0, %1, %2, %3, %4, %5, %6, %7, %8, %9, %10, %11, %12, %13, %14, %15, %16, %17, %18, %19, %20, %21, %22, %23, %24, %25, %26, %27, %28, %29, %30, %31}, %32, %33, p, 1, 1, %35, %36;\n}\n"
    : "+f"(d[0]), "+f"(d[1]), "+f"(d[2]), "+f"(d[3]), "+f"(d[4]), "+f"(d[5]), "+f"(d[6]), "+f"(d[7]), "+f"(d[8]), "+f"(d[9]), "+f"(d[10]), "+f"(d[11]), "+f"(d[12]), "+f"(d[13]), "+f"(d[14]), "+f"(d[15]), "+f"(d[16]), "+f"(d[17]), "+f"(d[18]), "+f"(d[19]), "+f"(d[20]), "+f"(d[21]), "+f"(d[22]), "+f"(d[23]), "+f"(d[24]), "+f"(d[25]), "+f"(d[26]), "+f"(d[27]), "+f"(d[28]), "+f"(d[29]), "+f"(d[30]), "+f"(d[31])
    : "l"(da), "l"(db), "r"(sd), "n"(TA), "n"(TB));
}
template<int TA, int TB> __device__ __forceinline__ void wgmma_ss_n128(float (&d)[64], uint64_t da, uint64_t db, int sd) {
  asm volatile("{\n.reg .pred p;\nsetp.ne.b32 p, %66, 0;\n"
    "wgmma.mma_async.sync.aligned.m64n128k16.f32.bf16.bf16 {%0, %1, %2, %3, %4, %5, %6, %7, %8, %9, %10, %11, %12, %13, %14, %15, %16, %17, %18, %19, %20, %21, %22, %23, %24, %25, %26, %27, %28, %29, %30, %31, %32, %33, %34, %35, %36, %37, %38, %39, %40, %41, %42, %43, %44, %45, %46, %47, %48, %49, %50, %51, %52, %53, %54, %55, %56, %57, %58, %59, %60, %61, %62, %63}, %64, %65, p, 1, 1, %67, %68;\n}\n"
    : "+f"(d[0]), "+f"(d[1]), "+f"(d[2]), "+f"(d[3]), "+f"(d[4]), "+f"(d[5]), "+f"(d[6]), "+f"(d[7]), "+f"(d[8]), "+f"(d[9]), "+f"(d[10]), "+f"(d[11]), "+f"(d[12]), "+f"(d[13]), "+f"(d[14]), "+f"(d[15]), "+f"(d[16]), "+f"(d[17]), "+f"(d[18]), "+f"(d[19]), "+f"(d[20]), "+f"(d[21]), "+f"(d[22]), "+f"(d[23]), "+f"(d[24]), "+f"(d[25]), "+f"(d[26]), "+f"(d[27]), "+f"(d[28]), "+f"(d[29]), "+f"(d[30]), "+f"(d[31]), "+f"(d[32]), "+f"(d[33]), "+f"(d[34]), "+f"(d[35]), "+f"(d[36]), "+f"(d[37]), "+f"(d[38]), "+f"(d[39]), "+f"(d[40]), "+f"(d[41]), "+f"(d[42]), "+f"(d[43]), "+f"(d[44]), "+f"(d[45]), "+f"(d[46]), "+f"(d[47]), "+f"(d[48]), "+f"(d[49]), "+f"(d[50]), "+f"(d[51]), "+f"(d[52]), "+f"(d[53]), "+f"(d[54]), "+f"(d[55]), "+f"(d[56]), "+f"(d[57]), "+f"(d[58]), "+f"(d[59]), "+f"(d[60]), "+f"(d[61]), "+f"(d[62]), "+f"(d[63])
    : "l"(da), "l"(db), "r"(sd), "n"(TA), "n"(TB));
}
template<int TA, int TB> __device__ __forceinline__ void wgmma_ss_n144(float (&d)[72], uint64_t da, uint64_t db, int sd) {
  asm volatile("{\n.reg .pred p;\nsetp.ne.b32 p, %74, 0;\n"
    "wgmma.mma_async.sync.aligned.m64n144k16.f32.bf16.bf16 {%0, %1, %2, %3, %4, %5, %6, %7, %8, %9, %10, %11, %12, %13, %14, %15, %16, %17, %18, %19, %20, %21, %22, %23, %24, %25, %26, %27, %28, %29, %30, %31, %32, %33, %34, %35, %36, %37, %38, %39, %40, %41, %42, %43, %44, %45, %46, %47, %48, %49, %50, %51, %52, %53, %54, %55, %56, %57, %58, %59, %60, %61, %62, %63, %64, %65, %66, %67, %68, %69, %70, %71}, %72, %73, p, 1, 1, %75, %76;\n}\n"
    : "+f"(d[0]), "+f"(d[1]), "+f"(d[2]), "+f"(d[3]), "+f"(d[4]), "+f"(d[5]), "+f"(d[6]), "+f"(d[7]), "+f"(d[8]), "+f"(d[9]), "+f"(d[10]), "+f"(d[11]), "+f"(d[12]), "+f"(d[13]), "+f"(d[14]), "+f"(d[15]), "+f"(d[16]), "+f"(d[17]), "+f"(d[18]), "+f"(d[19]), "+f"(d[20]), "+f"(d[21]), "+f"(d[22]), "+f"(d[23]), "+f"(d[24]), "+f"(d[25]), "+f"(d[26]), "+f"(d[27]), "+f"(d[28]), "+f"(d[29]), "+f"(d[30]), "+f"(d[31]), "+f"(d[32]), "+f"(d[33]), "+f"(d[34]), "+f"(d[35]), "+f"(d[36]), "+f"(d[37]), "+f"(d[38]), "+f"(d[39]), "+f"(d[40]), "+f"(d[41]), "+f"(d[42]), "+f"(d[43]), "+f"(d[44]), "+f"(d[45]), "+f"(d[46]), "+f"(d[47]), "+f"(d[48]), "+f"(d[49]), "+f"(d[50]), "+f"(d[51]), "+f"(d[52]), "+f"(d[53]), "+f"(d[54]), "+f"(d[55]), "+f"(d[56]), "+f"(d[57]), "+f"(d[58]), "+f"(d[59]), "+f"(d[60]), "+f"(d[61]), "+f"(d[62]), "+f"(d[63]), "+f"(d[64]), "+f"(d[65]), "+f"(d[66]), "+f"(d[67]), "+f"(d[68]), "+f"(d[69]), "+f"(d[70]), "+f"(d[71])
    : "l"(da), "l"(db), "r"(sd), "n"(TA), "n"(TB));
}
template<int TA, int TB> __device__ __forceinline__ void wgmma_ss_n160(float (&d)[80], uint64_t da, uint64_t db, int sd) {
  asm volatile("{\n.reg .pred p;\nsetp.ne.b32 p, %82, 0;\n"
    "wgmma.mma_async.sync.aligned.m64n160k16.f32.bf16.bf16 {%0, %1, %2, %3, %4, %5, %6, %7, %8, %9, %10, %11, %12, %13, %14, %15, %16, %17, %18, %19, %20, %21, %22, %23, %24, %25, %26, %27, %28, %29, %30, %31, %32, %33, %34, %35, %36, %37, %38, %39, %40, %41, %42, %43, %44, %45, %46, %47, %48, %49, %50, %51, %52, %53, %54, %55, %56, %57, %58, %59, %60, %61, %62, %63, %64, %65, %66, %67, %68, %69, %70, %71, %72, %73, %74, %75, %76, %77, %78, %79}, %80, %81, p, 1, 1, %83, %84;\n}\n"
    : "+f"(d[0]), "+f"(d[1]), "+f"(d[2]), "+f"(d[3]), "+f"(d[4]), "+f"(d[5]), "+f"(d[6]), "+f"(d[7]), "+f"(d[8]), "+f"(d[9]), "+f"(d[10]), "+f"(d[11]), "+f"(d[12]), "+f"(d[13]), "+f"(d[14]), "+f"(d[15]), "+f"(d[16]), "+f"(d[17]), "+f"(d[18]), "+f"(d[19]), "+f"(d[20]), "+f"(d[21]), "+f"(d[22]), "+f"(d[23]), "+f"(d[24]), "+f"(d[25]), "+f"(d[26]), "+f"(d[27]), "+f"(d[28]), "+f"(d[29]), "+f"(d[30]), "+f"(d[31]), "+f"(d[32]), "+f"(d[33]), "+f"(d[34]), "+f"(d[35]), "+f"(d[36]), "+f"(d[37]), "+f"(d[38]), "+f"(d[39]), "+f"(d[40]), "+f"(d[41]), "+f"(d[42]), "+f"(d[43]), "+f"(d[44]), "+f"(d[45]), "+f"(d[46]), "+f"(d[47]), "+f"(d[48]), "+f"(d[49]), "+f"(d[50]), "+f"(d[51]), "+f"(d[52]), "+f"(d[53]), "+f"(d[54]), "+f"(d[55]), "+f"(d[56]), "+f"(d[57]), "+f"(d[58]), "+f"(d[59]), "+f"(d[60]), "+f"(d[61]), "+f"(d[62]), "+f"(d[63]), "+f"(d[64]), "+f"(d[65]), "+f"(d[66]), "+f"(d[67]), "+f"(d[68]), "+f"(d[69]), "+f"(d[70]), "+f"(d[71]), "+f"(d[72]), "+f"(d[73]), "+f"(d[74]), "+f"(d[75]), "+f"(d[76]), "+f"(d[77]), "+f"(d[78]), "+f"(d[79])
    : "l"(da), "l"(db), "r"(sd), "n"(TA), "n"(TB));
}
template<int TB> __device__ __forceinline__ void wgmma_rs_n64(float (&d)[32], const uint32_t (&a)[4], uint64_t db, int sd) {
  asm volatile("{\n.reg .pred p;\nsetp.ne.b32 p, %37, 0;\n"
    "wgmma.mma_async.sync.aligned.m64n64k16.f32.bf16.bf16 {%0, %1, %2, %3, %4, %5, %6, %7, %8, %9, %10, %11, %12, %13, %14, %15, %16, %17, %18, %19, %20, %21, %22, %23, %24, %25, %26, %27, %28, %29, %30, %31}, {%32, %33, %34, %35}, %36, p, 1, 1, %38;\n}\n"
    : "+f"(d[0]), "+f"(d[1]), "+f"(d[2]), "+f"(d[3]), "+f"(d[4]), "+f"(d[5]), "+f"(d[6]), "+f"(d[7]), "+f"(d[8]), "+f"(d[9]), "+f"(d[10]), "+f"(d[11]), "+f"(d[12]), "+f"(d[13]), "+f"(d[14]), "+f"(d[15]), "+f"(d[16]), "+f"(d[17]), "+f"(d[18]), "+f"(d[19]), "+f"(d[20]), "+f"(d[21]), "+f"(d[22]), "+f"(d[23]), "+f"(d[24]), "+f"(d[25]), "+f"(d[26]), "+f"(d[27]), "+f"(d[28]), "+f"(d[29]), "+f"(d[30]), "+f"(d[31])
    : "r"(a[0]), "r"(a[1]), "r"(a[2]), "r"(a[3]), "l"(db), "r"(sd), "n"(TB));
}
template<int TB> __device__ __forceinline__ void wgmma_rs_n128(float (&d)[64], const uint32_t (&a)[4], uint64_t db, int sd) {
  asm volatile("{\n.reg .pred p;\nsetp.ne.b32 p, %69, 0;\n"
    "wgmma.mma_async.sync.aligned.m64n128k16.f32.bf16.bf16 {%0, %1, %2, %3, %4, %5, %6, %7, %8, %9, %10, %11, %12, %13, %14, %15, %16, %17, %18, %19, %20, %21, %22, %23, %24, %25, %26, %27, %28, %29, %30, %31, %32, %33, %34, %35, %36, %37, %38, %39, %40, %41, %42, %43, %44, %45, %46, %47, %48, %49, %50, %51, %52, %53, %54, %55, %56, %57, %58, %59, %60, %61, %62, %63}, {%64, %65, %66, %67}, %68, p, 1, 1, %70;\n}\n"
    : "+f"(d[0]), "+f"(d[1]), "+f"(d[2]), "+f"(d[3]), "+f"(d[4]), "+f"(d[5]), "+f"(d[6]), "+f"(d[7]), "+f"(d[8]), "+f"(d[9]), "+f"(d[10]), "+f"(d[11]), "+f"(d[12]), "+f"(d[13]), "+f"(d[14]), "+f"(d[15]), "+f"(d[16]), "+f"(d[17]), "+f"(d[18]), "+f"(d[19]), "+f"(d[20]), "+f"(d[21]), "+f"(d[22]), "+f"(d[23]), "+f"(d[24]), "+f"(d[25]), "+f"(d[26]), "+f"(d[27]), "+f"(d[28]), "+f"(d[29]), "+f"(d[30]), "+f"(d[31]), "+f"(d[32]), "+f"(d[33]), "+f"(d[34]), "+f"(d[35]), "+f"(d[36]), "+f"(d[37]), "+f"(d[38]), "+f"(d[39]), "+f"(d[40]), "+f"(d[41]), "+f"(d[42]), "+f"(d[43]), "+f"(d[44]), "+f"(d[45]), "+f"(d[46]), "+f"(d[47]), "+f"(d[48]), "+f"(d[49]), "+f"(d[50]), "+f"(d[51]), "+f"(d[52]), "+f"(d[53]), "+f"(d[54]), "+f"(d[55]), "+f"(d[56]), "+f"(d[57]), "+f"(d[58]), "+f"(d[59]), "+f"(d[60]), "+f"(d[61]), "+f"(d[62]), "+f"(d[63])
    : "r"(a[0]), "r"(a[1]), "r"(a[2]), "r"(a[3]), "l"(db), "r"(sd), "n"(TB));
}

__device__ __align__(128) const uint32_t T_F64[4096] = {
0x3f803f80,0x3f803f80,0x3f803f80,0x3f803f80,0x3f803f80,0x3f803f80,0x3f803f80,0x3f803f80,0x3f803f80,0x3f803f80,0x3f803f80,0x3f803f80,
0x3f803f80,0x3f803f80,0x3f803f80,0x3f803f80,0x3f803f80,0x3f803f80,0x3f803f80,0x3f803f80,0x3f803f80,0x3f803f80,0x3f803f80,0x3f803f80,
0x3f803f80,0x3f803f80,0x3f803f80,0x3f803f80,0x3f803f80,0x3f803f80,0x3f803f80,0x3f803f80,0x3f223f35,0x3ef13f0e,0x3e953ec4,0x3dc93e48,
0x3f7f3f80,0x3f753f7b,0x3f623f6d,0x3f463f55,0xbf46bf35,0xbf62bf55,0xbf75bf6d,0xbf7fbf7b,0xbdc90000,0xbe95be48,0xbef1bec4,0xbf22bf0e,
0xbf22bf35,0xbef1bf0e,0xbe95bec4,0xbdc9be48,0xbf7fbf80,0xbf75bf7b,0xbf62bf6d,0xbf46bf55,0x3f463f35,0x3f623f55,0x3f753f6d,0x3f7f3f7b,
0x3dc90000,0x3e953e48,0x3ef13ec4,0x3f223f0e,0xbf7bbf80,0xbf55bf6d,0xbf0ebf35,0xbe48bec4,0x3e480000,0x3f0e3ec4,0x3f553f35,0x3f7b3f6d,
0x3f7b3f80,0x3f553f6d,0x3f0e3f35,0x3e483ec4,0xbe480000,0xbf0ebec4,0xbf55bf35,0xbf7bbf6d,0xbf7bbf80,0xbf55bf6d,0xbf0ebf35,0xbe48bec4,
0x3e480000,0x3f0e3ec4,0x3f553f35,0x3f7b3f6d,0x3f7b3f80,0x3f553f6d,0x3f0e3f35,0x3e483ec4,0xbe480000,0xbf0ebec4,0xbf55bf35,0xbf7bbf6d,
0x3ef13f35,0xbdc93e48,0xbf22bec4,0xbf75bf55,0x3e950000,0x3f463f0e,0x3f7f3f6d,0x3f623f7b,0xbf62bf35,0xbf7fbf7b,0xbf46bf6d,0xbe95bf0e,
0x3f753f80,0x3f223f55,0x3dc93ec4,0xbef1be48,0xbef1bf35,0x3dc9be48,0x3f223ec4,0x3f753f55,0xbe950000,0xbf46bf0e,0xbf7fbf6d,0xbf62bf7b,
0x3f623f35,0x3f7f3f7b,0x3f463f6d,0x3e953f0e,0xbf75bf80,0xbf22bf55,0xbdc9bec4,0x3ef13e48,0x3f6d3f80,0x3ec43f35,0xbec40000,0xbf6dbf35,
0xbf6dbf80,0xbec4bf35,0x3ec40000,0x3f6d3f35,0x3f6d3f80,0x3ec43f35,0xbec40000,0xbf6dbf35,0xbf6dbf80,0xbec4bf35,0x3ec40000,0x3f6d3f35,
0x3f6d3f80,0x3ec43f35,0xbec40000,0xbf6dbf35,0xbf6dbf80,0xbec4bf35,0x3ec40000,0x3f6d3f35,0x3f6d3f80,0x3ec43f35,0xbec40000,0xbf6dbf35,
0xbf6dbf80,0xbec4bf35,0x3ec40000,0x3f6d3f35,0x3e953f35,0xbf22be48,0xbf7fbf6d,0xbef1bf55,0xbf62bf80,0xbdc9bf0e,0x3f463ec4,0x3f753f7b,
0xbf75bf35,0xbf46bf7b,0x3dc9bec4,0x3f623f0e,0x3ef10000,0x3f7f3f55,0x3f223f6d,0xbe953e48,0xbe95bf35,0x3f223e48,0x3f7f3f6d,0x3ef13f55,
0x3f623f80,0x3dc93f0e,0xbf46bec4,0xbf75bf7b,0x3f753f35,0x3f463f7b,0xbdc93ec4,0xbf62bf0e,0xbef10000,0xbf7fbf55,0xbf22bf6d,0x3e95be48,
0xbf55bf80,0x3e48bec4,0x3f7b3f35,0x3f0e3f6d,0xbf0e0000,0xbf7bbf6d,0xbe48bf35,0x3f553ec4,0x3f553f80,0xbe483ec4,0xbf7bbf35,0xbf0ebf6d,
0x3f0e0000,0x3f7b3f6d,0x3e483f35,0xbf55bec4,0xbf55bf80,0x3e48bec4,0x3f7b3f35,0x3f0e3f6d,0xbf0e0000,0xbf7bbf6d,0xbe48bf35,0x3f553ec4,
0x3f553f80,0xbe483ec4,0xbf7bbf35,0xbf0ebf6d,0x3f0e0000,0x3f7b3f6d,0x3e483f35,0xbf55bec4,0x3dc93f35,0xbf75bf0e,0xbef1bf6d,0x3f463e48,
0xbf220000,0xbf62bf7b,0x3e95bec4,0x3f7f3f55,0xbf7fbf35,0xbe95bf55,0x3f623ec4,0x3f223f7b,0xbf46bf80,0x3ef1be48,0x3f753f6d,0xbdc93f0e,
0xbdc9bf35,0x3f753f0e,0x3ef13f6d,0xbf46be48,0x3f220000,0x3f623f7b,0xbe953ec4,0xbf7fbf55,0x3f7f3f35,0x3e953f55,0xbf62bec4,0xbf22bf7b,
0x3f463f80,0xbef13e48,0xbf75bf6d,0x3dc9bf0e,0x3f353f80,0xbf350000,0xbf35bf80,0x3f350000,0x3f353f80,0xbf350000,0xbf35bf80,0x3f350000,
0x3f353f80,0xbf350000,0xbf35bf80,0x3f350000,0x3f353f80,0xbf350000,0xbf35bf80,0x3f350000,0x3f353f80,0xbf350000,0xbf35bf80,0x3f350000,
0x3f353f80,0xbf350000,0xbf35bf80,0x3f350000,0x3f353f80,0xbf350000,0xbf35bf80,0x3f350000,0x3f353f80,0xbf350000,0xbf35bf80,0x3f350000,
0xbdc93f35,0xbf75bf55,0x3ef1bec4,0x3f463f7b,0x3f223f80,0xbf62be48,0xbe95bf6d,0x3f7f3f0e,0xbf7fbf35,0x3e95bf0e,0x3f623f6d,0xbf223e48,
0xbf460000,0xbef1bf7b,0x3f753ec4,0x3dc93f55,0x3dc9bf35,0x3f753f55,0xbef13ec4,0xbf46bf7b,0xbf22bf80,0x3f623e48,0x3e953f6d,0xbf7fbf0e,
0x3f7f3f35,0xbe953f0e,0xbf62bf6d,0x3f22be48,0x3f460000,0x3ef13f7b,0xbf75bec4,0xbdc9bf55,0xbf0ebf80,0x3f7b3ec4,0xbe483f35,0xbf55bf6d,
0x3f550000,0x3e483f6d,0xbf7bbf35,0x3f0ebec4,0x3f0e3f80,0xbf7bbec4,0x3e48bf35,0x3f553f6d,0xbf550000,0xbe48bf6d,0x3f7b3f35,0xbf0e3ec4,
0xbf0ebf80,0x3f7b3ec4,0xbe483f35,0xbf55bf6d,0x3f550000,0x3e483f6d,0xbf7bbf35,0x3f0ebec4,0x3f0e3f80,0xbf7bbec4,0x3e48bf35,0x3f553f6d,
0xbf550000,0xbe48bf6d,0x3f7b3f35,0xbf0e3ec4,0xbe953f35,0xbf22bf7b,0x3f7f3ec4,0xbef13f0e,0x3f620000,0xbdc93f55,0xbf46bf6d,0x3f753e48,
0xbf75bf35,0x3f46be48,0x3dc93f6d,0xbf62bf55,0x3ef13f80,0xbf7fbf0e,0x3f22bec4,0x3e953f7b,0x3e95bf35,0x3f223f7b,0xbf7fbec4,0x3ef1bf0e,
0xbf620000,0x3dc9bf55,0x3f463f6d,0xbf75be48,0x3f753f35,0xbf463e48,0xbdc9bf6d,0x3f623f55,0xbef1bf80,0x3f7f3f0e,0xbf223ec4,0xbe95bf7b,
0x3ec43f80,0xbf6dbf35,0x3f6d0000,0xbec43f35,0xbec4bf80,0x3f6d3f35,0xbf6d0000,0x3ec4bf35,0x3ec43f80,0xbf6dbf35,0x3f6d0000,0xbec43f35,
0xbec4bf80,0x3f6d3f35,0xbf6d0000,0x3ec4bf35,0x3ec43f80,0xbf6dbf35,0x3f6d0000,0xbec43f35,0xbec4bf80,0x3f6d3f35,0xbf6d0000,0x3ec4bf35,
0x3ec43f80,0xbf6dbf35,0x3f6d0000,0xbec43f35,0xbec4bf80,0x3f6d3f35,0xbf6d0000,0x3ec4bf35,0xbef13f35,0xbdc9bf7b,0x3f223f6d,0xbf75bf0e,
0xbe95bf80,0x3f463f55,0xbf7fbec4,0x3f62be48,0xbf62bf35,0x3f7f3e48,0xbf463ec4,0x3e95bf55,0x3f750000,0xbf223f0e,0x3dc9bf6d,0x3ef13f7b,
0x3ef1bf35,0x3dc93f7b,0xbf22bf6d,0x3f753f0e,0x3e953f80,0xbf46bf55,0x3f7f3ec4,0xbf623e48,0x3f623f35,0xbf7fbe48,0x3f46bec4,0xbe953f55,
0xbf750000,0x3f22bf0e,0xbdc93f6d,0xbef1bf7b,0xbe48bf80,0x3f0e3f6d,0xbf55bf35,0x3f7b3ec4,0xbf7b0000,0x3f55bec4,0xbf0e3f35,0x3e48bf6d,
0x3e483f80,0xbf0ebf6d,0x3f553f35,0xbf7bbec4,0x3f7b0000,0xbf553ec4,0x3f0ebf35,0xbe483f6d,0xbe48bf80,0x3f0e3f6d,0xbf55bf35,0x3f7b3ec4,
0xbf7b0000,0x3f55bec4,0xbf0e3f35,0x3e48bf6d,0x3e483f80,0xbf0ebf6d,0x3f553f35,0xbf7bbec4,0x3f7b0000,0xbf553ec4,0x3f0ebf35,0xbe483f6d,
0xbf223f35,0x3ef1bf55,0xbe953f6d,0x3dc9bf7b,0xbf7f0000,0x3f75be48,0xbf623ec4,0x3f46bf0e,0xbf46bf35,0x3f623f0e,0xbf75bec4,0x3f7f3e48,
0xbdc9bf80,0x3e953f7b,0xbef1bf6d,0x3f223f55,0x3f22bf35,0xbef13f55,0x3e95bf6d,0xbdc93f7b,0x3f7f0000,0xbf753e48,0x3f62bec4,0xbf463f0e,
0x3f463f35,0xbf62bf0e,0x3f753ec4,0xbf7fbe48,0x3dc93f80,0xbe95bf7b,0x3ef13f6d,0xbf22bf55,0x3f80,0xbf80,0x3f80,0xbf80,
0x3f80,0xbf80,0x3f80,0xbf80,0x3f80,0xbf80,0x3f80,0xbf80,0x3f80,0xbf80,0x3f80,0xbf80,
0x3f80,0xbf80,0x3f80,0xbf80,0x3f80,0xbf80,0x3f80,0xbf80,0x3f80,0xbf80,0x3f80,0xbf80,
0x3f80,0xbf80,0x3f80,0xbf80,0xbf463f35,0x3f62bf0e,0xbf753ec4,0x3f7fbe48,0xbdc93f80,0x3e95bf7b,0xbef13f6d,0x3f22bf55,
0xbf22bf35,0x3ef13f55,0xbe95bf6d,0x3dc93f7b,0xbf7f0000,0x3f753e48,0xbf62bec4,0x3f463f0e,0x3f46bf35,0xbf623f0e,0x3f75bec4,0xbf7f3e48,
0x3dc9bf80,0xbe953f7b,0x3ef1bf6d,0xbf223f55,0x3f223f35,0xbef1bf55,0x3e953f6d,0xbdc9bf7b,0x3f7f0000,0xbf75be48,0x3f623ec4,0xbf46bf0e,
0x3e48bf80,0xbf0e3f6d,0x3f55bf35,0xbf7b3ec4,0x3f7b0000,0xbf55bec4,0x3f0e3f35,0xbe48bf6d,0xbe483f80,0x3f0ebf6d,0xbf553f35,0x3f7bbec4,
0xbf7b0000,0x3f553ec4,0xbf0ebf35,0x3e483f6d,0x3e48bf80,0xbf0e3f6d,0x3f55bf35,0xbf7b3ec4,0x3f7b0000,0xbf55bec4,0x3f0e3f35,0xbe48bf6d,
0xbe483f80,0x3f0ebf6d,0xbf553f35,0x3f7bbec4,0xbf7b0000,0x3f553ec4,0xbf0ebf35,0x3e483f6d,0xbf623f35,0x3f7fbe48,0xbf46bec4,0x3e953f55,
0x3f750000,0xbf22bf0e,0x3dc93f6d,0x3ef1bf7b,0xbef1bf35,0xbdc93f7b,0x3f22bf6d,0xbf753f0e,0xbe953f80,0x3f46bf55,0xbf7f3ec4,0x3f623e48,
0x3f62bf35,0xbf7f3e48,0x3f463ec4,0xbe95bf55,0xbf750000,0x3f223f0e,0xbdc9bf6d,0xbef13f7b,0x3ef13f35,0x3dc9bf7b,0xbf223f6d,0x3f75bf0e,
0x3e95bf80,0xbf463f55,0x3f7fbec4,0xbf62be48,0xbec43f80,0x3f6dbf35,0xbf6d0000,0x3ec43f35,0x3ec4bf80,0xbf6d3f35,0x3f6d0000,0xbec4bf35,
0xbec43f80,0x3f6dbf35,0xbf6d0000,0x3ec43f35,0x3ec4bf80,0xbf6d3f35,0x3f6d0000,0xbec4bf35,0xbec43f80,0x3f6dbf35,0xbf6d0000,0x3ec43f35,
0x3ec4bf80,0xbf6d3f35,0x3f6d0000,0xbec4bf35,0xbec43f80,0x3f6dbf35,0xbf6d0000,0x3ec43f35,0x3ec4bf80,0xbf6d3f35,0x3f6d0000,0xbec4bf35,
0xbf753f35,0x3f463e48,0x3dc9bf6d,0xbf623f55,0x3ef1bf80,0xbf7f3f0e,0x3f223ec4,0x3e95bf7b,0xbe95bf35,0xbf223f7b,0x3f7fbec4,0xbef1bf0e,
0x3f620000,0xbdc9bf55,0xbf463f6d,0x3f75be48,0x3f75bf35,0xbf46be48,0xbdc93f6d,0x3f62bf55,0xbef13f80,0x3f7fbf0e,0xbf22bec4,0xbe953f7b,
0x3e953f35,0x3f22bf7b,0xbf7f3ec4,0x3ef13f0e,0xbf620000,0x3dc93f55,0x3f46bf6d,0xbf753e48,0x3f0ebf80,0xbf7b3ec4,0x3e483f35,0x3f55bf6d,
0xbf550000,0xbe483f6d,0x3f7bbf35,0xbf0ebec4,0xbf0e3f80,0x3f7bbec4,0xbe48bf35,0xbf553f6d,0x3f550000,0x3e48bf6d,0xbf7b3f35,0x3f0e3ec4,
0x3f0ebf80,0xbf7b3ec4,0x3e483f35,0x3f55bf6d,0xbf550000,0xbe483f6d,0x3f7bbf35,0xbf0ebec4,0xbf0e3f80,0x3f7bbec4,0xbe48bf35,0xbf553f6d,
0x3f550000,0x3e48bf6d,0xbf7b3f35,0x3f0e3ec4,0xbf7f3f35,0x3e953f0e,0x3f62bf6d,0xbf22be48,0xbf460000,0xbef13f7b,0x3f75bec4,0x3dc9bf55,
0xbdc9bf35,0xbf753f55,0x3ef13ec4,0x3f46bf7b,0x3f22bf80,0xbf623e48,0xbe953f6d,0x3f7fbf0e,0x3f7fbf35,0xbe95bf0e,0xbf623f6d,0x3f223e48,
0x3f460000,0x3ef1bf7b,0xbf753ec4,0xbdc93f55,0x3dc93f35,0x3f75bf55,0xbef1bec4,0xbf463f7b,0xbf223f80,0x3f62be48,0x3e95bf6d,0xbf7f3f0e,
0xbf353f80,0x3f350000,0x3f35bf80,0xbf350000,0xbf353f80,0x3f350000,0x3f35bf80,0xbf350000,0xbf353f80,0x3f350000,0x3f35bf80,0xbf350000,
0xbf353f80,0x3f350000,0x3f35bf80,0xbf350000,0xbf353f80,0x3f350000,0x3f35bf80,0xbf350000,0xbf353f80,0x3f350000,0x3f35bf80,0xbf350000,
0xbf353f80,0x3f350000,0x3f35bf80,0xbf350000,0xbf353f80,0x3f350000,0x3f35bf80,0xbf350000,0xbf7f3f35,0xbe953f55,0x3f62bec4,0x3f22bf7b,
0xbf463f80,0x3ef13e48,0x3f75bf6d,0xbdc9bf0e,0x3dc9bf35,0xbf753f0e,0xbef13f6d,0x3f46be48,0xbf220000,0xbf623f7b,0x3e953ec4,0x3f7fbf55,
0x3f7fbf35,0x3e95bf55,0xbf623ec4,0xbf223f7b,0x3f46bf80,0xbef1be48,0xbf753f6d,0x3dc93f0e,0xbdc93f35,0x3f75bf0e,0x3ef1bf6d,0xbf463e48,
0x3f220000,0x3f62bf7b,0xbe95bec4,0xbf7f3f55,0x3f55bf80,0xbe48bec4,0xbf7b3f35,0xbf0e3f6d,0x3f0e0000,0x3f7bbf6d,0x3e48bf35,0xbf553ec4,
0xbf553f80,0x3e483ec4,0x3f7bbf35,0x3f0ebf6d,0xbf0e0000,0xbf7b3f6d,0xbe483f35,0x3f55bec4,0x3f55bf80,0xbe48bec4,0xbf7b3f35,0xbf0e3f6d,
0x3f0e0000,0x3f7bbf6d,0x3e48bf35,0xbf553ec4,0xbf553f80,0x3e483ec4,0x3f7bbf35,0x3f0ebf6d,0xbf0e0000,0xbf7b3f6d,0xbe483f35,0x3f55bec4,
0xbf753f35,0xbf463f7b,0x3dc93ec4,0x3f62bf0e,0x3ef10000,0x3f7fbf55,0x3f22bf6d,0xbe95be48,0x3e95bf35,0xbf223e48,0xbf7f3f6d,0xbef13f55,
0xbf623f80,0xbdc93f0e,0x3f46bec4,0x3f75bf7b,0x3f75bf35,0x3f46bf7b,0xbdc9bec4,0xbf623f0e,0xbef10000,0xbf7f3f55,0xbf223f6d,0x3e953e48,
0xbe953f35,0x3f22be48,0x3f7fbf6d,0x3ef1bf55,0x3f62bf80,0x3dc9bf0e,0xbf463ec4,0xbf753f7b,0xbf6d3f80,0xbec43f35,0x3ec40000,0x3f6dbf35,
0x3f6dbf80,0x3ec4bf35,0xbec40000,0xbf6d3f35,0xbf6d3f80,0xbec43f35,0x3ec40000,0x3f6dbf35,0x3f6dbf80,0x3ec4bf35,0xbec40000,0xbf6d3f35,
0xbf6d3f80,0xbec43f35,0x3ec40000,0x3f6dbf35,0x3f6dbf80,0x3ec4bf35,0xbec40000,0xbf6d3f35,0xbf6d3f80,0xbec43f35,0x3ec40000,0x3f6dbf35,
0x3f6dbf80,0x3ec4bf35,0xbec40000,0xbf6d3f35,0xbf623f35,0xbf7f3f7b,0xbf463f6d,0xbe953f0e,0x3f75bf80,0x3f22bf55,0x3dc9bec4,0xbef13e48,
0x3ef1bf35,0xbdc9be48,0xbf223ec4,0xbf753f55,0x3e950000,0x3f46bf0e,0x3f7fbf6d,0x3f62bf7b,0x3f62bf35,0x3f7fbf7b,0x3f46bf6d,0x3e95bf0e,
0xbf753f80,0xbf223f55,0xbdc93ec4,0x3ef1be48,0xbef13f35,0x3dc93e48,0x3f22bec4,0x3f75bf55,0xbe950000,0xbf463f0e,0xbf7f3f6d,0xbf623f7b,
0x3f7bbf80,0x3f55bf6d,0x3f0ebf35,0x3e48bec4,0xbe480000,0xbf0e3ec4,0xbf553f35,0xbf7b3f6d,0xbf7b3f80,0xbf553f6d,0xbf0e3f35,0xbe483ec4,
0x3e480000,0x3f0ebec4,0x3f55bf35,0x3f7bbf6d,0x3f7bbf80,0x3f55bf6d,0x3f0ebf35,0x3e48bec4,0xbe480000,0xbf0e3ec4,0xbf553f35,0xbf7b3f6d,
0xbf7b3f80,0xbf553f6d,0xbf0e3f35,0xbe483ec4,0x3e480000,0x3f0ebec4,0x3f55bf35,0x3f7bbf6d,0xbf463f35,0xbf623f55,0xbf753f6d,0xbf7f3f7b,
0xbdc90000,0xbe953e48,0xbef13ec4,0xbf223f0e,0x3f22bf35,0x3ef1bf0e,0x3e95bec4,0x3dc9be48,0x3f7fbf80,0x3f75bf7b,0x3f62bf6d,0x3f46bf55,
0x3f46bf35,0x3f62bf55,0x3f75bf6d,0x3f7fbf7b,0x3dc90000,0x3e95be48,0x3ef1bec4,0x3f22bf0e,0xbf223f35,0xbef13f0e,0xbe953ec4,0xbdc93e48,
0xbf7f3f80,0xbf753f7b,0xbf623f6d,0xbf463f55,0xbf803f80,0xbf803f80,0xbf803f80,0xbf803f80,0xbf803f80,0xbf803f80,0xbf803f80,0xbf803f80,
0xbf803f80,0xbf803f80,0xbf803f80,0xbf803f80,0xbf803f80,0xbf803f80,0xbf803f80,0xbf803f80,0xbf803f80,0xbf803f80,0xbf803f80,0xbf803f80,
0xbf803f80,0xbf803f80,0xbf803f80,0xbf803f80,0xbf803f80,0xbf803f80,0xbf803f80,0xbf803f80,0xbf803f80,0xbf803f80,0xbf803f80,0xbf803f80,
0xbf223f35,0xbef13f0e,0xbe953ec4,0xbdc93e48,0xbf7f3f80,0xbf753f7b,0xbf623f6d,0xbf463f55,0x3f46bf35,0x3f62bf55,0x3f75bf6d,0x3f7fbf7b,
0x3dc90000,0x3e95be48,0x3ef1bec4,0x3f22bf0e,0x3f22bf35,0x3ef1bf0e,0x3e95bec4,0x3dc9be48,0x3f7fbf80,0x3f75bf7b,0x3f62bf6d,0x3f46bf55,
0xbf463f35,0xbf623f55,0xbf753f6d,0xbf7f3f7b,0xbdc90000,0xbe953e48,0xbef13ec4,0xbf223f0e,0x3f7bbf80,0x3f55bf6d,0x3f0ebf35,0x3e48bec4,
0xbe480000,0xbf0e3ec4,0xbf553f35,0xbf7b3f6d,0xbf7b3f80,0xbf553f6d,0xbf0e3f35,0xbe483ec4,0x3e480000,0x3f0ebec4,0x3f55bf35,0x3f7bbf6d,
0x3f7bbf80,0x3f55bf6d,0x3f0ebf35,0x3e48bec4,0xbe480000,0xbf0e3ec4,0xbf553f35,0xbf7b3f6d,0xbf7b3f80,0xbf553f6d,0xbf0e3f35,0xbe483ec4,
0x3e480000,0x3f0ebec4,0x3f55bf35,0x3f7bbf6d,0xbef13f35,0x3dc93e48,0x3f22bec4,0x3f75bf55,0xbe950000,0xbf463f0e,0xbf7f3f6d,0xbf623f7b,
0x3f62bf35,0x3f7fbf7b,0x3f46bf6d,0x3e95bf0e,0xbf753f80,0xbf223f55,0xbdc93ec4,0x3ef1be48,0x3ef1bf35,0xbdc9be48,0xbf223ec4,0xbf753f55,
0x3e950000,0x3f46bf0e,0x3f7fbf6d,0x3f62bf7b,0xbf623f35,0xbf7f3f7b,0xbf463f6d,0xbe953f0e,0x3f75bf80,0x3f22bf55,0x3dc9bec4,0xbef13e48,
0xbf6d3f80,0xbec43f35,0x3ec40000,0x3f6dbf35,0x3f6dbf80,0x3ec4bf35,0xbec40000,0xbf6d3f35,0xbf6d3f80,0xbec43f35,0x3ec40000,0x3f6dbf35,
0x3f6dbf80,0x3ec4bf35,0xbec40000,0xbf6d3f35,0xbf6d3f80,0xbec43f35,0x3ec40000,0x3f6dbf35,0x3f6dbf80,0x3ec4bf35,0xbec40000,0xbf6d3f35,
0xbf6d3f80,0xbec43f35,0x3ec40000,0x3f6dbf35,0x3f6dbf80,0x3ec4bf35,0xbec40000,0xbf6d3f35,0xbe953f35,0x3f22be48,0x3f7fbf6d,0x3ef1bf55,
0x3f62bf80,0x3dc9bf0e,0xbf463ec4,0xbf753f7b,0x3f75bf35,0x3f46bf7b,0xbdc9bec4,0xbf623f0e,0xbef10000,0xbf7f3f55,0xbf223f6d,0x3e953e48,
0x3e95bf35,0xbf223e48,0xbf7f3f6d,0xbef13f55,0xbf623f80,0xbdc93f0e,0x3f46bec4,0x3f75bf7b,0xbf753f35,0xbf463f7b,0x3dc93ec4,0x3f62bf0e,
0x3ef10000,0x3f7fbf55,0x3f22bf6d,0xbe95be48,0x3f55bf80,0xbe48bec4,0xbf7b3f35,0xbf0e3f6d,0x3f0e0000,0x3f7bbf6d,0x3e48bf35,0xbf553ec4,
0xbf553f80,0x3e483ec4,0x3f7bbf35,0x3f0ebf6d,0xbf0e0000,0xbf7b3f6d,0xbe483f35,0x3f55bec4,0x3f55bf80,0xbe48bec4,0xbf7b3f35,0xbf0e3f6d,
0x3f0e0000,0x3f7bbf6d,0x3e48bf35,0xbf553ec4,0xbf553f80,0x3e483ec4,0x3f7bbf35,0x3f0ebf6d,0xbf0e0000,0xbf7b3f6d,0xbe483f35,0x3f55bec4,
0xbdc93f35,0x3f75bf0e,0x3ef1bf6d,0xbf463e48,0x3f220000,0x3f62bf7b,0xbe95bec4,0xbf7f3f55,0x3f7fbf35,0x3e95bf55,0xbf623ec4,0xbf223f7b,
0x3f46bf80,0xbef1be48,0xbf753f6d,0x3dc93f0e,0x3dc9bf35,0xbf753f0e,0xbef13f6d,0x3f46be48,0xbf220000,0xbf623f7b,0x3e953ec4,0x3f7fbf55,
0xbf7f3f35,0xbe953f55,0x3f62bec4,0x3f22bf7b,0xbf463f80,0x3ef13e48,0x3f75bf6d,0xbdc9bf0e,0xbf353f80,0x3f350000,0x3f35bf80,0xbf350000,
0xbf353f80,0x3f350000,0x3f35bf80,0xbf350000,0xbf353f80,0x3f350000,0x3f35bf80,0xbf350000,0xbf353f80,0x3f350000,0x3f35bf80,0xbf350000,
0xbf353f80,0x3f350000,0x3f35bf80,0xbf350000,0xbf353f80,0x3f350000,0x3f35bf80,0xbf350000,0xbf353f80,0x3f350000,0x3f35bf80,0xbf350000,
0xbf353f80,0x3f350000,0x3f35bf80,0xbf350000,0x3dc93f35,0x3f75bf55,0xbef1bec4,0xbf463f7b,0xbf223f80,0x3f62be48,0x3e95bf6d,0xbf7f3f0e,
0x3f7fbf35,0xbe95bf0e,0xbf623f6d,0x3f223e48,0x3f460000,0x3ef1bf7b,0xbf753ec4,0xbdc93f55,0xbdc9bf35,0xbf753f55,0x3ef13ec4,0x3f46bf7b,
0x3f22bf80,0xbf623e48,0xbe953f6d,0x3f7fbf0e,0xbf7f3f35,0x3e953f0e,0x3f62bf6d,0xbf22be48,0xbf460000,0xbef13f7b,0x3f75bec4,0x3dc9bf55,
0x3f0ebf80,0xbf7b3ec4,0x3e483f35,0x3f55bf6d,0xbf550000,0xbe483f6d,0x3f7bbf35,0xbf0ebec4,0xbf0e3f80,0x3f7bbec4,0xbe48bf35,0xbf553f6d,
0x3f550000,0x3e48bf6d,0xbf7b3f35,0x3f0e3ec4,0x3f0ebf80,0xbf7b3ec4,0x3e483f35,0x3f55bf6d,0xbf550000,0xbe483f6d,0x3f7bbf35,0xbf0ebec4,
0xbf0e3f80,0x3f7bbec4,0xbe48bf35,0xbf553f6d,0x3f550000,0x3e48bf6d,0xbf7b3f35,0x3f0e3ec4,0x3e953f35,0x3f22bf7b,0xbf7f3ec4,0x3ef13f0e,
0xbf620000,0x3dc93f55,0x3f46bf6d,0xbf753e48,0x3f75bf35,0xbf46be48,0xbdc93f6d,0x3f62bf55,0xbef13f80,0x3f7fbf0e,0xbf22bec4,0xbe953f7b,
0xbe95bf35,0xbf223f7b,0x3f7fbec4,0xbef1bf0e,0x3f620000,0xbdc9bf55,0xbf463f6d,0x3f75be48,0xbf753f35,0x3f463e48,0x3dc9bf6d,0xbf623f55,
0x3ef1bf80,0xbf7f3f0e,0x3f223ec4,0x3e95bf7b,0xbec43f80,0x3f6dbf35,0xbf6d0000,0x3ec43f35,0x3ec4bf80,0xbf6d3f35,0x3f6d0000,0xbec4bf35,
0xbec43f80,0x3f6dbf35,0xbf6d0000,0x3ec43f35,0x3ec4bf80,0xbf6d3f35,0x3f6d0000,0xbec4bf35,0xbec43f80,0x3f6dbf35,0xbf6d0000,0x3ec43f35,
0x3ec4bf80,0xbf6d3f35,0x3f6d0000,0xbec4bf35,0xbec43f80,0x3f6dbf35,0xbf6d0000,0x3ec43f35,0x3ec4bf80,0xbf6d3f35,0x3f6d0000,0xbec4bf35,
0x3ef13f35,0x3dc9bf7b,0xbf223f6d,0x3f75bf0e,0x3e95bf80,0xbf463f55,0x3f7fbec4,0xbf62be48,0x3f62bf35,0xbf7f3e48,0x3f463ec4,0xbe95bf55,
0xbf750000,0x3f223f0e,0xbdc9bf6d,0xbef13f7b,0xbef1bf35,0xbdc93f7b,0x3f22bf6d,0xbf753f0e,0xbe953f80,0x3f46bf55,0xbf7f3ec4,0x3f623e48,
0xbf623f35,0x3f7fbe48,0xbf46bec4,0x3e953f55,0x3f750000,0xbf22bf0e,0x3dc93f6d,0x3ef1bf7b,0x3e48bf80,0xbf0e3f6d,0x3f55bf35,0xbf7b3ec4,
0x3f7b0000,0xbf55bec4,0x3f0e3f35,0xbe48bf6d,0xbe483f80,0x3f0ebf6d,0xbf553f35,0x3f7bbec4,0xbf7b0000,0x3f553ec4,0xbf0ebf35,0x3e483f6d,
0x3e48bf80,0xbf0e3f6d,0x3f55bf35,0xbf7b3ec4,0x3f7b0000,0xbf55bec4,0x3f0e3f35,0xbe48bf6d,0xbe483f80,0x3f0ebf6d,0xbf553f35,0x3f7bbec4,
0xbf7b0000,0x3f553ec4,0xbf0ebf35,0x3e483f6d,0x3f223f35,0xbef1bf55,0x3e953f6d,0xbdc9bf7b,0x3f7f0000,0xbf75be48,0x3f623ec4,0xbf46bf0e,
0x3f46bf35,0xbf623f0e,0x3f75bec4,0xbf7f3e48,0x3dc9bf80,0xbe953f7b,0x3ef1bf6d,0xbf223f55,0xbf22bf35,0x3ef13f55,0xbe95bf6d,0x3dc93f7b,
0xbf7f0000,0x3f753e48,0xbf62bec4,0x3f463f0e,0xbf463f35,0x3f62bf0e,0xbf753ec4,0x3f7fbe48,0xbdc93f80,0x3e95bf7b,0xbef13f6d,0x3f22bf55,
0x3f80,0xbf80,0x3f80,0xbf80,0x3f80,0xbf80,0x3f80,0xbf80,0x3f80,0xbf80,0x3f80,0xbf80,
0x3f80,0xbf80,0x3f80,0xbf80,0x3f80,0xbf80,0x3f80,0xbf80,0x3f80,0xbf80,0x3f80,0xbf80,
0x3f80,0xbf80,0x3f80,0xbf80,0x3f80,0xbf80,0x3f80,0xbf80,0x3f463f35,0xbf62bf0e,0x3f753ec4,0xbf7fbe48,
0x3dc93f80,0xbe95bf7b,0x3ef13f6d,0xbf22bf55,0x3f22bf35,0xbef13f55,0x3e95bf6d,0xbdc93f7b,0x3f7f0000,0xbf753e48,0x3f62bec4,0xbf463f0e,
0xbf46bf35,0x3f623f0e,0xbf75bec4,0x3f7f3e48,0xbdc9bf80,0x3e953f7b,0xbef1bf6d,0x3f223f55,0xbf223f35,0x3ef1bf55,0xbe953f6d,0x3dc9bf7b,
0xbf7f0000,0x3f75be48,0xbf623ec4,0x3f46bf0e,0xbe48bf80,0x3f0e3f6d,0xbf55bf35,0x3f7b3ec4,0xbf7b0000,0x3f55bec4,0xbf0e3f35,0x3e48bf6d,
0x3e483f80,0xbf0ebf6d,0x3f553f35,0xbf7bbec4,0x3f7b0000,0xbf553ec4,0x3f0ebf35,0xbe483f6d,0xbe48bf80,0x3f0e3f6d,0xbf55bf35,0x3f7b3ec4,
0xbf7b0000,0x3f55bec4,0xbf0e3f35,0x3e48bf6d,0x3e483f80,0xbf0ebf6d,0x3f553f35,0xbf7bbec4,0x3f7b0000,0xbf553ec4,0x3f0ebf35,0xbe483f6d,
0x3f623f35,0xbf7fbe48,0x3f46bec4,0xbe953f55,0xbf750000,0x3f22bf0e,0xbdc93f6d,0xbef1bf7b,0x3ef1bf35,0x3dc93f7b,0xbf22bf6d,0x3f753f0e,
0x3e953f80,0xbf46bf55,0x3f7f3ec4,0xbf623e48,0xbf62bf35,0x3f7f3e48,0xbf463ec4,0x3e95bf55,0x3f750000,0xbf223f0e,0x3dc9bf6d,0x3ef13f7b,
0xbef13f35,0xbdc9bf7b,0x3f223f6d,0xbf75bf0e,0xbe95bf80,0x3f463f55,0xbf7fbec4,0x3f62be48,0x3ec43f80,0xbf6dbf35,0x3f6d0000,0xbec43f35,
0xbec4bf80,0x3f6d3f35,0xbf6d0000,0x3ec4bf35,0x3ec43f80,0xbf6dbf35,0x3f6d0000,0xbec43f35,0xbec4bf80,0x3f6d3f35,0xbf6d0000,0x3ec4bf35,
0x3ec43f80,0xbf6dbf35,0x3f6d0000,0xbec43f35,0xbec4bf80,0x3f6d3f35,0xbf6d0000,0x3ec4bf35,0x3ec43f80,0xbf6dbf35,0x3f6d0000,0xbec43f35,
0xbec4bf80,0x3f6d3f35,0xbf6d0000,0x3ec4bf35,0x3f753f35,0xbf463e48,0xbdc9bf6d,0x3f623f55,0xbef1bf80,0x3f7f3f0e,0xbf223ec4,0xbe95bf7b,
0x3e95bf35,0x3f223f7b,0xbf7fbec4,0x3ef1bf0e,0xbf620000,0x3dc9bf55,0x3f463f6d,0xbf75be48,0xbf75bf35,0x3f46be48,0x3dc93f6d,0xbf62bf55,
0x3ef13f80,0xbf7fbf0e,0x3f22bec4,0x3e953f7b,0xbe953f35,0xbf22bf7b,0x3f7f3ec4,0xbef13f0e,0x3f620000,0xbdc93f55,0xbf46bf6d,0x3f753e48,
0xbf0ebf80,0x3f7b3ec4,0xbe483f35,0xbf55bf6d,0x3f550000,0x3e483f6d,0xbf7bbf35,0x3f0ebec4,0x3f0e3f80,0xbf7bbec4,0x3e48bf35,0x3f553f6d,
0xbf550000,0xbe48bf6d,0x3f7b3f35,0xbf0e3ec4,0xbf0ebf80,0x3f7b3ec4,0xbe483f35,0xbf55bf6d,0x3f550000,0x3e483f6d,0xbf7bbf35,0x3f0ebec4,
0x3f0e3f80,0xbf7bbec4,0x3e48bf35,0x3f553f6d,0xbf550000,0xbe48bf6d,0x3f7b3f35,0xbf0e3ec4,0x3f7f3f35,0xbe953f0e,0xbf62bf6d,0x3f22be48,
0x3f460000,0x3ef13f7b,0xbf75bec4,0xbdc9bf55,0x3dc9bf35,0x3f753f55,0xbef13ec4,0xbf46bf7b,0xbf22bf80,0x3f623e48,0x3e953f6d,0xbf7fbf0e,
0xbf7fbf35,0x3e95bf0e,0x3f623f6d,0xbf223e48,0xbf460000,0xbef1bf7b,0x3f753ec4,0x3dc93f55,0xbdc93f35,0xbf75bf55,0x3ef1bec4,0x3f463f7b,
0x3f223f80,0xbf62be48,0xbe95bf6d,0x3f7f3f0e,0x3f353f80,0xbf350000,0xbf35bf80,0x3f350000,0x3f353f80,0xbf350000,0xbf35bf80,0x3f350000,
0x3f353f80,0xbf350000,0xbf35bf80,0x3f350000,0x3f353f80,0xbf350000,0xbf35bf80,0x3f350000,0x3f353f80,0xbf350000,0xbf35bf80,0x3f350000,
0x3f353f80,0xbf350000,0xbf35bf80,0x3f350000,0x3f353f80,0xbf350000,0xbf35bf80,0x3f350000,0x3f353f80,0xbf350000,0xbf35bf80,0x3f350000,
0x3f7f3f35,0x3e953f55,0xbf62bec4,0xbf22bf7b,0x3f463f80,0xbef13e48,0xbf75bf6d,0x3dc9bf0e,0xbdc9bf35,0x3f753f0e,0x3ef13f6d,0xbf46be48,
0x3f220000,0x3f623f7b,0xbe953ec4,0xbf7fbf55,0xbf7fbf35,0xbe95bf55,0x3f623ec4,0x3f223f7b,0xbf46bf80,0x3ef1be48,0x3f753f6d,0xbdc93f0e,
0x3dc93f35,0xbf75bf0e,0xbef1bf6d,0x3f463e48,0xbf220000,0xbf62bf7b,0x3e95bec4,0x3f7f3f55,0xbf55bf80,0x3e48bec4,0x3f7b3f35,0x3f0e3f6d,
0xbf0e0000,0xbf7bbf6d,0xbe48bf35,0x3f553ec4,0x3f553f80,0xbe483ec4,0xbf7bbf35,0xbf0ebf6d,0x3f0e0000,0x3f7b3f6d,0x3e483f35,0xbf55bec4,
0xbf55bf80,0x3e48bec4,0x3f7b3f35,0x3f0e3f6d,0xbf0e0000,0xbf7bbf6d,0xbe48bf35,0x3f553ec4,0x3f553f80,0xbe483ec4,0xbf7bbf35,0xbf0ebf6d,
0x3f0e0000,0x3f7b3f6d,0x3e483f35,0xbf55bec4,0x3f753f35,0x3f463f7b,0xbdc93ec4,0xbf62bf0e,0xbef10000,0xbf7fbf55,0xbf22bf6d,0x3e95be48,
0xbe95bf35,0x3f223e48,0x3f7f3f6d,0x3ef13f55,0x3f623f80,0x3dc93f0e,0xbf46bec4,0xbf75bf7b,0xbf75bf35,0xbf46bf7b,0x3dc9bec4,0x3f623f0e,
0x3ef10000,0x3f7f3f55,0x3f223f6d,0xbe953e48,0x3e953f35,0xbf22be48,0xbf7fbf6d,0xbef1bf55,0xbf62bf80,0xbdc9bf0e,0x3f463ec4,0x3f753f7b,
0x3f6d3f80,0x3ec43f35,0xbec40000,0xbf6dbf35,0xbf6dbf80,0xbec4bf35,0x3ec40000,0x3f6d3f35,0x3f6d3f80,0x3ec43f35,0xbec40000,0xbf6dbf35,
0xbf6dbf80,0xbec4bf35,0x3ec40000,0x3f6d3f35,0x3f6d3f80,0x3ec43f35,0xbec40000,0xbf6dbf35,0xbf6dbf80,0xbec4bf35,0x3ec40000,0x3f6d3f35,
0x3f6d3f80,0x3ec43f35,0xbec40000,0xbf6dbf35,0xbf6dbf80,0xbec4bf35,0x3ec40000,0x3f6d3f35,0x3f623f35,0x3f7f3f7b,0x3f463f6d,0x3e953f0e,
0xbf75bf80,0xbf22bf55,0xbdc9bec4,0x3ef13e48,0xbef1bf35,0x3dc9be48,0x3f223ec4,0x3f753f55,0xbe950000,0xbf46bf0e,0xbf7fbf6d,0xbf62bf7b,
0xbf62bf35,0xbf7fbf7b,0xbf46bf6d,0xbe95bf0e,0x3f753f80,0x3f223f55,0x3dc93ec4,0xbef1be48,0x3ef13f35,0xbdc93e48,0xbf22bec4,0xbf75bf55,
0x3e950000,0x3f463f0e,0x3f7f3f6d,0x3f623f7b,0xbf7bbf80,0xbf55bf6d,0xbf0ebf35,0xbe48bec4,0x3e480000,0x3f0e3ec4,0x3f553f35,0x3f7b3f6d,
0x3f7b3f80,0x3f553f6d,0x3f0e3f35,0x3e483ec4,0xbe480000,0xbf0ebec4,0xbf55bf35,0xbf7bbf6d,0xbf7bbf80,0xbf55bf6d,0xbf0ebf35,0xbe48bec4,
0x3e480000,0x3f0e3ec4,0x3f553f35,0x3f7b3f6d,0x3f7b3f80,0x3f553f6d,0x3f0e3f35,0x3e483ec4,0xbe480000,0xbf0ebec4,0xbf55bf35,0xbf7bbf6d,
0x3f463f35,0x3f623f55,0x3f753f6d,0x3f7f3f7b,0x3dc90000,0x3e953e48,0x3ef13ec4,0x3f223f0e,0xbf22bf35,0xbef1bf0e,0xbe95bec4,0xbdc9be48,
0xbf7fbf80,0xbf75bf7b,0xbf62bf6d,0xbf46bf55,0xbf46bf35,0xbf62bf55,0xbf75bf6d,0xbf7fbf7b,0xbdc90000,0xbe95be48,0xbef1bec4,0xbf22bf0e,
0x3f223f35,0x3ef13f0e,0x3e953ec4,0x3dc93e48,0x3f7f3f80,0x3f753f7b,0x3f623f6d,0x3f463f55,0x0,0x0,0x0,0x0,
0x0,0x0,0x0,0x0,0x0,0x0,0x0,0x0,0x0,0x0,0x0,0x0,
0x0,0x0,0x0,0x0,0x0,0x0,0x0,0x0,0x0,0x0,0x0,0x0,
0x0,0x0,0x0,0x0,0xbf46bf35,0xbf62bf55,0xbf75bf6d,0xbf7fbf7b,0xbdc90000,0xbe95be48,0xbef1bec4,0xbf22bf0e,
0xbf22bf35,0xbef1bf0e,0xbe95bec4,0xbdc9be48,0xbf7fbf80,0xbf75bf7b,0xbf62bf6d,0xbf46bf55,0x3f463f35,0x3f623f55,0x3f753f6d,0x3f7f3f7b,
0x3dc90000,0x3e953e48,0x3ef13ec4,0x3f223f0e,0x3f223f35,0x3ef13f0e,0x3e953ec4,0x3dc93e48,0x3f7f3f80,0x3f753f7b,0x3f623f6d,0x3f463f55,
0x3e480000,0x3f0e3ec4,0x3f553f35,0x3f7b3f6d,0x3f7b3f80,0x3f553f6d,0x3f0e3f35,0x3e483ec4,0xbe480000,0xbf0ebec4,0xbf55bf35,0xbf7bbf6d,
0xbf7bbf80,0xbf55bf6d,0xbf0ebf35,0xbe48bec4,0x3e480000,0x3f0e3ec4,0x3f553f35,0x3f7b3f6d,0x3f7b3f80,0x3f553f6d,0x3f0e3f35,0x3e483ec4,
0xbe480000,0xbf0ebec4,0xbf55bf35,0xbf7bbf6d,0xbf7bbf80,0xbf55bf6d,0xbf0ebf35,0xbe48bec4,0xbf62bf35,0xbf7fbf7b,0xbf46bf6d,0xbe95bf0e,
0x3f753f80,0x3f223f55,0x3dc93ec4,0xbef1be48,0xbef1bf35,0x3dc9be48,0x3f223ec4,0x3f753f55,0xbe950000,0xbf46bf0e,0xbf7fbf6d,0xbf62bf7b,
0x3f623f35,0x3f7f3f7b,0x3f463f6d,0x3e953f0e,0xbf75bf80,0xbf22bf55,0xbdc9bec4,0x3ef13e48,0x3ef13f35,0xbdc93e48,0xbf22bec4,0xbf75bf55,
0x3e950000,0x3f463f0e,0x3f7f3f6d,0x3f623f7b,0xbec40000,0xbf6dbf35,0xbf6dbf80,0xbec4bf35,0x3ec40000,0x3f6d3f35,0x3f6d3f80,0x3ec43f35,
0xbec40000,0xbf6dbf35,0xbf6dbf80,0xbec4bf35,0x3ec40000,0x3f6d3f35,0x3f6d3f80,0x3ec43f35,0xbec40000,0xbf6dbf35,0xbf6dbf80,0xbec4bf35,
0x3ec40000,0x3f6d3f35,0x3f6d3f80,0x3ec43f35,0xbec40000,0xbf6dbf35,0xbf6dbf80,0xbec4bf35,0x3ec40000,0x3f6d3f35,0x3f6d3f80,0x3ec43f35,
0xbf75bf35,0xbf46bf7b,0x3dc9bec4,0x3f623f0e,0x3ef10000,0x3f7f3f55,0x3f223f6d,0xbe953e48,0xbe95bf35,0x3f223e48,0x3f7f3f6d,0x3ef13f55,
0x3f623f80,0x3dc93f0e,0xbf46bec4,0xbf75bf7b,0x3f753f35,0x3f463f7b,0xbdc93ec4,0xbf62bf0e,0xbef10000,0xbf7fbf55,0xbf22bf6d,0x3e95be48,
0x3e953f35,0xbf22be48,0xbf7fbf6d,0xbef1bf55,0xbf62bf80,0xbdc9bf0e,0x3f463ec4,0x3f753f7b,0x3f0e0000,0x3f7b3f6d,0x3e483f35,0xbf55bec4,
0xbf55bf80,0x3e48bec4,0x3f7b3f35,0x3f0e3f6d,0xbf0e0000,0xbf7bbf6d,0xbe48bf35,0x3f553ec4,0x3f553f80,0xbe483ec4,0xbf7bbf35,0xbf0ebf6d,
0x3f0e0000,0x3f7b3f6d,0x3e483f35,0xbf55bec4,0xbf55bf80,0x3e48bec4,0x3f7b3f35,0x3f0e3f6d,0xbf0e0000,0xbf7bbf6d,0xbe48bf35,0x3f553ec4,
0x3f553f80,0xbe483ec4,0xbf7bbf35,0xbf0ebf6d,0xbf7fbf35,0xbe95bf55,0x3f623ec4,0x3f223f7b,0xbf46bf80,0x3ef1be48,0x3f753f6d,0xbdc93f0e,
0xbdc9bf35,0x3f753f0e,0x3ef13f6d,0xbf46be48,0x3f220000,0x3f623f7b,0xbe953ec4,0xbf7fbf55,0x3f7f3f35,0x3e953f55,0xbf62bec4,0xbf22bf7b,
0x3f463f80,0xbef13e48,0xbf75bf6d,0x3dc9bf0e,0x3dc93f35,0xbf75bf0e,0xbef1bf6d,0x3f463e48,0xbf220000,0xbf62bf7b,0x3e95bec4,0x3f7f3f55,
0xbf350000,0xbf35bf80,0x3f350000,0x3f353f80,0xbf350000,0xbf35bf80,0x3f350000,0x3f353f80,0xbf350000,0xbf35bf80,0x3f350000,0x3f353f80,
0xbf350000,0xbf35bf80,0x3f350000,0x3f353f80,0xbf350000,0xbf35bf80,0x3f350000,0x3f353f80,0xbf350000,0xbf35bf80,0x3f350000,0x3f353f80,
0xbf350000,0xbf35bf80,0x3f350000,0x3f353f80,0xbf350000,0xbf35bf80,0x3f350000,0x3f353f80,0xbf7fbf35,0x3e95bf0e,0x3f623f6d,0xbf223e48,
0xbf460000,0xbef1bf7b,0x3f753ec4,0x3dc93f55,0x3dc9bf35,0x3f753f55,0xbef13ec4,0xbf46bf7b,0xbf22bf80,0x3f623e48,0x3e953f6d,0xbf7fbf0e,
0x3f7f3f35,0xbe953f0e,0xbf62bf6d,0x3f22be48,0x3f460000,0x3ef13f7b,0xbf75bec4,0xbdc9bf55,0xbdc93f35,0xbf75bf55,0x3ef1bec4,0x3f463f7b,
0x3f223f80,0xbf62be48,0xbe95bf6d,0x3f7f3f0e,0x3f550000,0x3e483f6d,0xbf7bbf35,0x3f0ebec4,0x3f0e3f80,0xbf7bbec4,0x3e48bf35,0x3f553f6d,
0xbf550000,0xbe48bf6d,0x3f7b3f35,0xbf0e3ec4,0xbf0ebf80,0x3f7b3ec4,0xbe483f35,0xbf55bf6d,0x3f550000,0x3e483f6d,0xbf7bbf35,0x3f0ebec4,
0x3f0e3f80,0xbf7bbec4,0x3e48bf35,0x3f553f6d,0xbf550000,0xbe48bf6d,0x3f7b3f35,0xbf0e3ec4,0xbf0ebf80,0x3f7b3ec4,0xbe483f35,0xbf55bf6d,
0xbf75bf35,0x3f46be48,0x3dc93f6d,0xbf62bf55,0x3ef13f80,0xbf7fbf0e,0x3f22bec4,0x3e953f7b,0x3e95bf35,0x3f223f7b,0xbf7fbec4,0x3ef1bf0e,
0xbf620000,0x3dc9bf55,0x3f463f6d,0xbf75be48,0x3f753f35,0xbf463e48,0xbdc9bf6d,0x3f623f55,0xbef1bf80,0x3f7f3f0e,0xbf223ec4,0xbe95bf7b,
0xbe953f35,0xbf22bf7b,0x3f7f3ec4,0xbef13f0e,0x3f620000,0xbdc93f55,0xbf46bf6d,0x3f753e48,0xbf6d0000,0x3ec4bf35,0x3ec43f80,0xbf6dbf35,
0x3f6d0000,0xbec43f35,0xbec4bf80,0x3f6d3f35,0xbf6d0000,0x3ec4bf35,0x3ec43f80,0xbf6dbf35,0x3f6d0000,0xbec43f35,0xbec4bf80,0x3f6d3f35,
0xbf6d0000,0x3ec4bf35,0x3ec43f80,0xbf6dbf35,0x3f6d0000,0xbec43f35,0xbec4bf80,0x3f6d3f35,0xbf6d0000,0x3ec4bf35,0x3ec43f80,0xbf6dbf35,
0x3f6d0000,0xbec43f35,0xbec4bf80,0x3f6d3f35,0xbf62bf35,0x3f7f3e48,0xbf463ec4,0x3e95bf55,0x3f750000,0xbf223f0e,0x3dc9bf6d,0x3ef13f7b,
0x3ef1bf35,0x3dc93f7b,0xbf22bf6d,0x3f753f0e,0x3e953f80,0xbf46bf55,0x3f7f3ec4,0xbf623e48,0x3f623f35,0xbf7fbe48,0x3f46bec4,0xbe953f55,
0xbf750000,0x3f22bf0e,0xbdc93f6d,0xbef1bf7b,0xbef13f35,0xbdc9bf7b,0x3f223f6d,0xbf75bf0e,0xbe95bf80,0x3f463f55,0xbf7fbec4,0x3f62be48,
0x3f7b0000,0xbf553ec4,0x3f0ebf35,0xbe483f6d,0xbe48bf80,0x3f0e3f6d,0xbf55bf35,0x3f7b3ec4,0xbf7b0000,0x3f55bec4,0xbf0e3f35,0x3e48bf6d,
0x3e483f80,0xbf0ebf6d,0x3f553f35,0xbf7bbec4,0x3f7b0000,0xbf553ec4,0x3f0ebf35,0xbe483f6d,0xbe48bf80,0x3f0e3f6d,0xbf55bf35,0x3f7b3ec4,
0xbf7b0000,0x3f55bec4,0xbf0e3f35,0x3e48bf6d,0x3e483f80,0xbf0ebf6d,0x3f553f35,0xbf7bbec4,0xbf46bf35,0x3f623f0e,0xbf75bec4,0x3f7f3e48,
0xbdc9bf80,0x3e953f7b,0xbef1bf6d,0x3f223f55,0x3f22bf35,0xbef13f55,0x3e95bf6d,0xbdc93f7b,0x3f7f0000,0xbf753e48,0x3f62bec4,0xbf463f0e,
0x3f463f35,0xbf62bf0e,0x3f753ec4,0xbf7fbe48,0x3dc93f80,0xbe95bf7b,0x3ef13f6d,0xbf22bf55,0xbf223f35,0x3ef1bf55,0xbe953f6d,0x3dc9bf7b,
0xbf7f0000,0x3f75be48,0xbf623ec4,0x3f46bf0e,0xbf800000,0x3f800000,0xbf800000,0x3f800000,0xbf800000,0x3f800000,0xbf800000,0x3f800000,
0xbf800000,0x3f800000,0xbf800000,0x3f800000,0xbf800000,0x3f800000,0xbf800000,0x3f800000,0xbf800000,0x3f800000,0xbf800000,0x3f800000,
0xbf800000,0x3f800000,0xbf800000,0x3f800000,0xbf800000,0x3f800000,0xbf800000,0x3f800000,0xbf800000,0x3f800000,0xbf800000,0x3f800000,
0xbf22bf35,0x3ef13f55,0xbe95bf6d,0x3dc93f7b,0xbf7f0000,0x3f753e48,0xbf62bec4,0x3f463f0e,0x3f46bf35,0xbf623f0e,0x3f75bec4,0xbf7f3e48,
0x3dc9bf80,0xbe953f7b,0x3ef1bf6d,0xbf223f55,0x3f223f35,0xbef1bf55,0x3e953f6d,0xbdc9bf7b,0x3f7f0000,0xbf75be48,0x3f623ec4,0xbf46bf0e,
0xbf463f35,0x3f62bf0e,0xbf753ec4,0x3f7fbe48,0xbdc93f80,0x3e95bf7b,0xbef13f6d,0x3f22bf55,0x3f7b0000,0xbf55bec4,0x3f0e3f35,0xbe48bf6d,
0xbe483f80,0x3f0ebf6d,0xbf553f35,0x3f7bbec4,0xbf7b0000,0x3f553ec4,0xbf0ebf35,0x3e483f6d,0x3e48bf80,0xbf0e3f6d,0x3f55bf35,0xbf7b3ec4,
0x3f7b0000,0xbf55bec4,0x3f0e3f35,0xbe48bf6d,0xbe483f80,0x3f0ebf6d,0xbf553f35,0x3f7bbec4,0xbf7b0000,0x3f553ec4,0xbf0ebf35,0x3e483f6d,
0x3e48bf80,0xbf0e3f6d,0x3f55bf35,0xbf7b3ec4,0xbef1bf35,0xbdc93f7b,0x3f22bf6d,0xbf753f0e,0xbe953f80,0x3f46bf55,0xbf7f3ec4,0x3f623e48,
0x3f62bf35,0xbf7f3e48,0x3f463ec4,0xbe95bf55,0xbf750000,0x3f223f0e,0xbdc9bf6d,0xbef13f7b,0x3ef13f35,0x3dc9bf7b,0xbf223f6d,0x3f75bf0e,
0x3e95bf80,0xbf463f55,0x3f7fbec4,0xbf62be48,0xbf623f35,0x3f7fbe48,0xbf46bec4,0x3e953f55,0x3f750000,0xbf22bf0e,0x3dc93f6d,0x3ef1bf7b,
0xbf6d0000,0x3ec43f35,0x3ec4bf80,0xbf6d3f35,0x3f6d0000,0xbec4bf35,0xbec43f80,0x3f6dbf35,0xbf6d0000,0x3ec43f35,0x3ec4bf80,0xbf6d3f35,
0x3f6d0000,0xbec4bf35,0xbec43f80,0x3f6dbf35,0xbf6d0000,0x3ec43f35,0x3ec4bf80,0xbf6d3f35,0x3f6d0000,0xbec4bf35,0xbec43f80,0x3f6dbf35,
0xbf6d0000,0x3ec43f35,0x3ec4bf80,0xbf6d3f35,0x3f6d0000,0xbec4bf35,0xbec43f80,0x3f6dbf35,0xbe95bf35,0xbf223f7b,0x3f7fbec4,0xbef1bf0e,
0x3f620000,0xbdc9bf55,0xbf463f6d,0x3f75be48,0x3f75bf35,0xbf46be48,0xbdc93f6d,0x3f62bf55,0xbef13f80,0x3f7fbf0e,0xbf22bec4,0xbe953f7b,
0x3e953f35,0x3f22bf7b,0xbf7f3ec4,0x3ef13f0e,0xbf620000,0x3dc93f55,0x3f46bf6d,0xbf753e48,0xbf753f35,0x3f463e48,0x3dc9bf6d,0xbf623f55,
0x3ef1bf80,0xbf7f3f0e,0x3f223ec4,0x3e95bf7b,0x3f550000,0x3e48bf6d,0xbf7b3f35,0x3f0e3ec4,0x3f0ebf80,0xbf7b3ec4,0x3e483f35,0x3f55bf6d,
0xbf550000,0xbe483f6d,0x3f7bbf35,0xbf0ebec4,0xbf0e3f80,0x3f7bbec4,0xbe48bf35,0xbf553f6d,0x3f550000,0x3e48bf6d,0xbf7b3f35,0x3f0e3ec4,
0x3f0ebf80,0xbf7b3ec4,0x3e483f35,0x3f55bf6d,0xbf550000,0xbe483f6d,0x3f7bbf35,0xbf0ebec4,0xbf0e3f80,0x3f7bbec4,0xbe48bf35,0xbf553f6d,
0xbdc9bf35,0xbf753f55,0x3ef13ec4,0x3f46bf7b,0x3f22bf80,0xbf623e48,0xbe953f6d,0x3f7fbf0e,0x3f7fbf35,0xbe95bf0e,0xbf623f6d,0x3f223e48,
0x3f460000,0x3ef1bf7b,0xbf753ec4,0xbdc93f55,0x3dc93f35,0x3f75bf55,0xbef1bec4,0xbf463f7b,0xbf223f80,0x3f62be48,0x3e95bf6d,0xbf7f3f0e,
0xbf7f3f35,0x3e953f0e,0x3f62bf6d,0xbf22be48,0xbf460000,0xbef13f7b,0x3f75bec4,0x3dc9bf55,0xbf350000,0xbf353f80,0x3f350000,0x3f35bf80,
0xbf350000,0xbf353f80,0x3f350000,0x3f35bf80,0xbf350000,0xbf353f80,0x3f350000,0x3f35bf80,0xbf350000,0xbf353f80,0x3f350000,0x3f35bf80,
0xbf350000,0xbf353f80,0x3f350000,0x3f35bf80,0xbf350000,0xbf353f80,0x3f350000,0x3f35bf80,0xbf350000,0xbf353f80,0x3f350000,0x3f35bf80,
0xbf350000,0xbf353f80,0x3f350000,0x3f35bf80,0x3dc9bf35,0xbf753f0e,0xbef13f6d,0x3f46be48,0xbf220000,0xbf623f7b,0x3e953ec4,0x3f7fbf55,
0x3f7fbf35,0x3e95bf55,0xbf623ec4,0xbf223f7b,0x3f46bf80,0xbef1be48,0xbf753f6d,0x3dc93f0e,0xbdc93f35,0x3f75bf0e,0x3ef1bf6d,0xbf463e48,
0x3f220000,0x3f62bf7b,0xbe95bec4,0xbf7f3f55,0xbf7f3f35,0xbe953f55,0x3f62bec4,0x3f22bf7b,0xbf463f80,0x3ef13e48,0x3f75bf6d,0xbdc9bf0e,
0x3f0e0000,0x3f7bbf6d,0x3e48bf35,0xbf553ec4,0xbf553f80,0x3e483ec4,0x3f7bbf35,0x3f0ebf6d,0xbf0e0000,0xbf7b3f6d,0xbe483f35,0x3f55bec4,
0x3f55bf80,0xbe48bec4,0xbf7b3f35,0xbf0e3f6d,0x3f0e0000,0x3f7bbf6d,0x3e48bf35,0xbf553ec4,0xbf553f80,0x3e483ec4,0x3f7bbf35,0x3f0ebf6d,
0xbf0e0000,0xbf7b3f6d,0xbe483f35,0x3f55bec4,0x3f55bf80,0xbe48bec4,0xbf7b3f35,0xbf0e3f6d,0x3e95bf35,0xbf223e48,0xbf7f3f6d,0xbef13f55,
0xbf623f80,0xbdc93f0e,0x3f46bec4,0x3f75bf7b,0x3f75bf35,0x3f46bf7b,0xbdc9bec4,0xbf623f0e,0xbef10000,0xbf7f3f55,0xbf223f6d,0x3e953e48,
0xbe953f35,0x3f22be48,0x3f7fbf6d,0x3ef1bf55,0x3f62bf80,0x3dc9bf0e,0xbf463ec4,0xbf753f7b,0xbf753f35,0xbf463f7b,0x3dc93ec4,0x3f62bf0e,
0x3ef10000,0x3f7fbf55,0x3f22bf6d,0xbe95be48,0xbec40000,0xbf6d3f35,0xbf6d3f80,0xbec43f35,0x3ec40000,0x3f6dbf35,0x3f6dbf80,0x3ec4bf35,
0xbec40000,0xbf6d3f35,0xbf6d3f80,0xbec43f35,0x3ec40000,0x3f6dbf35,0x3f6dbf80,0x3ec4bf35,0xbec40000,0xbf6d3f35,0xbf6d3f80,0xbec43f35,
0x3ec40000,0x3f6dbf35,0x3f6dbf80,0x3ec4bf35,0xbec40000,0xbf6d3f35,0xbf6d3f80,0xbec43f35,0x3ec40000,0x3f6dbf35,0x3f6dbf80,0x3ec4bf35,
0x3ef1bf35,0xbdc9be48,0xbf223ec4,0xbf753f55,0x3e950000,0x3f46bf0e,0x3f7fbf6d,0x3f62bf7b,0x3f62bf35,0x3f7fbf7b,0x3f46bf6d,0x3e95bf0e,
0xbf753f80,0xbf223f55,0xbdc93ec4,0x3ef1be48,0xbef13f35,0x3dc93e48,0x3f22bec4,0x3f75bf55,0xbe950000,0xbf463f0e,0xbf7f3f6d,0xbf623f7b,
0xbf623f35,0xbf7f3f7b,0xbf463f6d,0xbe953f0e,0x3f75bf80,0x3f22bf55,0x3dc9bec4,0xbef13e48,0x3e480000,0x3f0ebec4,0x3f55bf35,0x3f7bbf6d,
0x3f7bbf80,0x3f55bf6d,0x3f0ebf35,0x3e48bec4,0xbe480000,0xbf0e3ec4,0xbf553f35,0xbf7b3f6d,0xbf7b3f80,0xbf553f6d,0xbf0e3f35,0xbe483ec4,
0x3e480000,0x3f0ebec4,0x3f55bf35,0x3f7bbf6d,0x3f7bbf80,0x3f55bf6d,0x3f0ebf35,0x3e48bec4,0xbe480000,0xbf0e3ec4,0xbf553f35,0xbf7b3f6d,
0xbf7b3f80,0xbf553f6d,0xbf0e3f35,0xbe483ec4,0x3f22bf35,0x3ef1bf0e,0x3e95bec4,0x3dc9be48,0x3f7fbf80,0x3f75bf7b,0x3f62bf6d,0x3f46bf55,
0x3f46bf35,0x3f62bf55,0x3f75bf6d,0x3f7fbf7b,0x3dc90000,0x3e95be48,0x3ef1bec4,0x3f22bf0e,0xbf223f35,0xbef13f0e,0xbe953ec4,0xbdc93e48,
0xbf7f3f80,0xbf753f7b,0xbf623f6d,0xbf463f55,0xbf463f35,0xbf623f55,0xbf753f6d,0xbf7f3f7b,0xbdc90000,0xbe953e48,0xbef13ec4,0xbf223f0e,
0x0,0x0,0x0,0x0,0x0,0x0,0x0,0x0,0x0,0x0,0x0,0x0,
0x0,0x0,0x0,0x0,0x0,0x0,0x0,0x0,0x0,0x0,0x0,0x0,
0x0,0x0,0x0,0x0,0x0,0x0,0x0,0x0,0x3f46bf35,0x3f62bf55,0x3f75bf6d,0x3f7fbf7b,
0x3dc90000,0x3e95be48,0x3ef1bec4,0x3f22bf0e,0x3f22bf35,0x3ef1bf0e,0x3e95bec4,0x3dc9be48,0x3f7fbf80,0x3f75bf7b,0x3f62bf6d,0x3f46bf55,
0xbf463f35,0xbf623f55,0xbf753f6d,0xbf7f3f7b,0xbdc90000,0xbe953e48,0xbef13ec4,0xbf223f0e,0xbf223f35,0xbef13f0e,0xbe953ec4,0xbdc93e48,
0xbf7f3f80,0xbf753f7b,0xbf623f6d,0xbf463f55,0xbe480000,0xbf0e3ec4,0xbf553f35,0xbf7b3f6d,0xbf7b3f80,0xbf553f6d,0xbf0e3f35,0xbe483ec4,
0x3e480000,0x3f0ebec4,0x3f55bf35,0x3f7bbf6d,0x3f7bbf80,0x3f55bf6d,0x3f0ebf35,0x3e48bec4,0xbe480000,0xbf0e3ec4,0xbf553f35,0xbf7b3f6d,
0xbf7b3f80,0xbf553f6d,0xbf0e3f35,0xbe483ec4,0x3e480000,0x3f0ebec4,0x3f55bf35,0x3f7bbf6d,0x3f7bbf80,0x3f55bf6d,0x3f0ebf35,0x3e48bec4,
0x3f62bf35,0x3f7fbf7b,0x3f46bf6d,0x3e95bf0e,0xbf753f80,0xbf223f55,0xbdc93ec4,0x3ef1be48,0x3ef1bf35,0xbdc9be48,0xbf223ec4,0xbf753f55,
0x3e950000,0x3f46bf0e,0x3f7fbf6d,0x3f62bf7b,0xbf623f35,0xbf7f3f7b,0xbf463f6d,0xbe953f0e,0x3f75bf80,0x3f22bf55,0x3dc9bec4,0xbef13e48,
0xbef13f35,0x3dc93e48,0x3f22bec4,0x3f75bf55,0xbe950000,0xbf463f0e,0xbf7f3f6d,0xbf623f7b,0x3ec40000,0x3f6dbf35,0x3f6dbf80,0x3ec4bf35,
0xbec40000,0xbf6d3f35,0xbf6d3f80,0xbec43f35,0x3ec40000,0x3f6dbf35,0x3f6dbf80,0x3ec4bf35,0xbec40000,0xbf6d3f35,0xbf6d3f80,0xbec43f35,
0x3ec40000,0x3f6dbf35,0x3f6dbf80,0x3ec4bf35,0xbec40000,0xbf6d3f35,0xbf6d3f80,0xbec43f35,0x3ec40000,0x3f6dbf35,0x3f6dbf80,0x3ec4bf35,
0xbec40000,0xbf6d3f35,0xbf6d3f80,0xbec43f35,0x3f75bf35,0x3f46bf7b,0xbdc9bec4,0xbf623f0e,0xbef10000,0xbf7f3f55,0xbf223f6d,0x3e953e48,
0x3e95bf35,0xbf223e48,0xbf7f3f6d,0xbef13f55,0xbf623f80,0xbdc93f0e,0x3f46bec4,0x3f75bf7b,0xbf753f35,0xbf463f7b,0x3dc93ec4,0x3f62bf0e,
0x3ef10000,0x3f7fbf55,0x3f22bf6d,0xbe95be48,0xbe953f35,0x3f22be48,0x3f7fbf6d,0x3ef1bf55,0x3f62bf80,0x3dc9bf0e,0xbf463ec4,0xbf753f7b,
0xbf0e0000,0xbf7b3f6d,0xbe483f35,0x3f55bec4,0x3f55bf80,0xbe48bec4,0xbf7b3f35,0xbf0e3f6d,0x3f0e0000,0x3f7bbf6d,0x3e48bf35,0xbf553ec4,
0xbf553f80,0x3e483ec4,0x3f7bbf35,0x3f0ebf6d,0xbf0e0000,0xbf7b3f6d,0xbe483f35,0x3f55bec4,0x3f55bf80,0xbe48bec4,0xbf7b3f35,0xbf0e3f6d,
0x3f0e0000,0x3f7bbf6d,0x3e48bf35,0xbf553ec4,0xbf553f80,0x3e483ec4,0x3f7bbf35,0x3f0ebf6d,0x3f7fbf35,0x3e95bf55,0xbf623ec4,0xbf223f7b,
0x3f46bf80,0xbef1be48,0xbf753f6d,0x3dc93f0e,0x3dc9bf35,0xbf753f0e,0xbef13f6d,0x3f46be48,0xbf220000,0xbf623f7b,0x3e953ec4,0x3f7fbf55,
0xbf7f3f35,0xbe953f55,0x3f62bec4,0x3f22bf7b,0xbf463f80,0x3ef13e48,0x3f75bf6d,0xbdc9bf0e,0xbdc93f35,0x3f75bf0e,0x3ef1bf6d,0xbf463e48,
0x3f220000,0x3f62bf7b,0xbe95bec4,0xbf7f3f55,0x3f350000,0x3f35bf80,0xbf350000,0xbf353f80,0x3f350000,0x3f35bf80,0xbf350000,0xbf353f80,
0x3f350000,0x3f35bf80,0xbf350000,0xbf353f80,0x3f350000,0x3f35bf80,0xbf350000,0xbf353f80,0x3f350000,0x3f35bf80,0xbf350000,0xbf353f80,
0x3f350000,0x3f35bf80,0xbf350000,0xbf353f80,0x3f350000,0x3f35bf80,0xbf350000,0xbf353f80,0x3f350000,0x3f35bf80,0xbf350000,0xbf353f80,
0x3f7fbf35,0xbe95bf0e,0xbf623f6d,0x3f223e48,0x3f460000,0x3ef1bf7b,0xbf753ec4,0xbdc93f55,0xbdc9bf35,0xbf753f55,0x3ef13ec4,0x3f46bf7b,
0x3f22bf80,0xbf623e48,0xbe953f6d,0x3f7fbf0e,0xbf7f3f35,0x3e953f0e,0x3f62bf6d,0xbf22be48,0xbf460000,0xbef13f7b,0x3f75bec4,0x3dc9bf55,
0x3dc93f35,0x3f75bf55,0xbef1bec4,0xbf463f7b,0xbf223f80,0x3f62be48,0x3e95bf6d,0xbf7f3f0e,0xbf550000,0xbe483f6d,0x3f7bbf35,0xbf0ebec4,
0xbf0e3f80,0x3f7bbec4,0xbe48bf35,0xbf553f6d,0x3f550000,0x3e48bf6d,0xbf7b3f35,0x3f0e3ec4,0x3f0ebf80,0xbf7b3ec4,0x3e483f35,0x3f55bf6d,
0xbf550000,0xbe483f6d,0x3f7bbf35,0xbf0ebec4,0xbf0e3f80,0x3f7bbec4,0xbe48bf35,0xbf553f6d,0x3f550000,0x3e48bf6d,0xbf7b3f35,0x3f0e3ec4,
0x3f0ebf80,0xbf7b3ec4,0x3e483f35,0x3f55bf6d,0x3f75bf35,0xbf46be48,0xbdc93f6d,0x3f62bf55,0xbef13f80,0x3f7fbf0e,0xbf22bec4,0xbe953f7b,
0xbe95bf35,0xbf223f7b,0x3f7fbec4,0xbef1bf0e,0x3f620000,0xbdc9bf55,0xbf463f6d,0x3f75be48,0xbf753f35,0x3f463e48,0x3dc9bf6d,0xbf623f55,
0x3ef1bf80,0xbf7f3f0e,0x3f223ec4,0x3e95bf7b,0x3e953f35,0x3f22bf7b,0xbf7f3ec4,0x3ef13f0e,0xbf620000,0x3dc93f55,0x3f46bf6d,0xbf753e48,
0x3f6d0000,0xbec4bf35,0xbec43f80,0x3f6dbf35,0xbf6d0000,0x3ec43f35,0x3ec4bf80,0xbf6d3f35,0x3f6d0000,0xbec4bf35,0xbec43f80,0x3f6dbf35,
0xbf6d0000,0x3ec43f35,0x3ec4bf80,0xbf6d3f35,0x3f6d0000,0xbec4bf35,0xbec43f80,0x3f6dbf35,0xbf6d0000,0x3ec43f35,0x3ec4bf80,0xbf6d3f35,
0x3f6d0000,0xbec4bf35,0xbec43f80,0x3f6dbf35,0xbf6d0000,0x3ec43f35,0x3ec4bf80,0xbf6d3f35,0x3f62bf35,0xbf7f3e48,0x3f463ec4,0xbe95bf55,
0xbf750000,0x3f223f0e,0xbdc9bf6d,0xbef13f7b,0xbef1bf35,0xbdc93f7b,0x3f22bf6d,0xbf753f0e,0xbe953f80,0x3f46bf55,0xbf7f3ec4,0x3f623e48,
0xbf623f35,0x3f7fbe48,0xbf46bec4,0x3e953f55,0x3f750000,0xbf22bf0e,0x3dc93f6d,0x3ef1bf7b,0x3ef13f35,0x3dc9bf7b,0xbf223f6d,0x3f75bf0e,
0x3e95bf80,0xbf463f55,0x3f7fbec4,0xbf62be48,0xbf7b0000,0x3f553ec4,0xbf0ebf35,0x3e483f6d,0x3e48bf80,0xbf0e3f6d,0x3f55bf35,0xbf7b3ec4,
0x3f7b0000,0xbf55bec4,0x3f0e3f35,0xbe48bf6d,0xbe483f80,0x3f0ebf6d,0xbf553f35,0x3f7bbec4,0xbf7b0000,0x3f553ec4,0xbf0ebf35,0x3e483f6d,
0x3e48bf80,0xbf0e3f6d,0x3f55bf35,0xbf7b3ec4,0x3f7b0000,0xbf55bec4,0x3f0e3f35,0xbe48bf6d,0xbe483f80,0x3f0ebf6d,0xbf553f35,0x3f7bbec4,
0x3f46bf35,0xbf623f0e,0x3f75bec4,0xbf7f3e48,0x3dc9bf80,0xbe953f7b,0x3ef1bf6d,0xbf223f55,0xbf22bf35,0x3ef13f55,0xbe95bf6d,0x3dc93f7b,
0xbf7f0000,0x3f753e48,0xbf62bec4,0x3f463f0e,0xbf463f35,0x3f62bf0e,0xbf753ec4,0x3f7fbe48,0xbdc93f80,0x3e95bf7b,0xbef13f6d,0x3f22bf55,
0x3f223f35,0xbef1bf55,0x3e953f6d,0xbdc9bf7b,0x3f7f0000,0xbf75be48,0x3f623ec4,0xbf46bf0e,0x3f800000,0xbf800000,0x3f800000,0xbf800000,
0x3f800000,0xbf800000,0x3f800000,0xbf800000,0x3f800000,0xbf800000,0x3f800000,0xbf800000,0x3f800000,0xbf800000,0x3f800000,0xbf800000,
0x3f800000,0xbf800000,0x3f800000,0xbf800000,0x3f800000,0xbf800000,0x3f800000,0xbf800000,0x3f800000,0xbf800000,0x3f800000,0xbf800000,
0x3f800000,0xbf800000,0x3f800000,0xbf800000,0x3f22bf35,0xbef13f55,0x3e95bf6d,0xbdc93f7b,0x3f7f0000,0xbf753e48,0x3f62bec4,0xbf463f0e,
0xbf46bf35,0x3f623f0e,0xbf75bec4,0x3f7f3e48,0xbdc9bf80,0x3e953f7b,0xbef1bf6d,0x3f223f55,0xbf223f35,0x3ef1bf55,0xbe953f6d,0x3dc9bf7b,
0xbf7f0000,0x3f75be48,0xbf623ec4,0x3f46bf0e,0x3f463f35,0xbf62bf0e,0x3f753ec4,0xbf7fbe48,0x3dc93f80,0xbe95bf7b,0x3ef13f6d,0xbf22bf55,
0xbf7b0000,0x3f55bec4,0xbf0e3f35,0x3e48bf6d,0x3e483f80,0xbf0ebf6d,0x3f553f35,0xbf7bbec4,0x3f7b0000,0xbf553ec4,0x3f0ebf35,0xbe483f6d,
0xbe48bf80,0x3f0e3f6d,0xbf55bf35,0x3f7b3ec4,0xbf7b0000,0x3f55bec4,0xbf0e3f35,0x3e48bf6d,0x3e483f80,0xbf0ebf6d,0x3f553f35,0xbf7bbec4,
0x3f7b0000,0xbf553ec4,0x3f0ebf35,0xbe483f6d,0xbe48bf80,0x3f0e3f6d,0xbf55bf35,0x3f7b3ec4,0x3ef1bf35,0x3dc93f7b,0xbf22bf6d,0x3f753f0e,
0x3e953f80,0xbf46bf55,0x3f7f3ec4,0xbf623e48,0xbf62bf35,0x3f7f3e48,0xbf463ec4,0x3e95bf55,0x3f750000,0xbf223f0e,0x3dc9bf6d,0x3ef13f7b,
0xbef13f35,0xbdc9bf7b,0x3f223f6d,0xbf75bf0e,0xbe95bf80,0x3f463f55,0xbf7fbec4,0x3f62be48,0x3f623f35,0xbf7fbe48,0x3f46bec4,0xbe953f55,
0xbf750000,0x3f22bf0e,0xbdc93f6d,0xbef1bf7b,0x3f6d0000,0xbec43f35,0xbec4bf80,0x3f6d3f35,0xbf6d0000,0x3ec4bf35,0x3ec43f80,0xbf6dbf35,
0x3f6d0000,0xbec43f35,0xbec4bf80,0x3f6d3f35,0xbf6d0000,0x3ec4bf35,0x3ec43f80,0xbf6dbf35,0x3f6d0000,0xbec43f35,0xbec4bf80,0x3f6d3f35,
0xbf6d0000,0x3ec4bf35,0x3ec43f80,0xbf6dbf35,0x3f6d0000,0xbec43f35,0xbec4bf80,0x3f6d3f35,0xbf6d0000,0x3ec4bf35,0x3ec43f80,0xbf6dbf35,
0x3e95bf35,0x3f223f7b,0xbf7fbec4,0x3ef1bf0e,0xbf620000,0x3dc9bf55,0x3f463f6d,0xbf75be48,0xbf75bf35,0x3f46be48,0x3dc93f6d,0xbf62bf55,
0x3ef13f80,0xbf7fbf0e,0x3f22bec4,0x3e953f7b,0xbe953f35,0xbf22bf7b,0x3f7f3ec4,0xbef13f0e,0x3f620000,0xbdc93f55,0xbf46bf6d,0x3f753e48,
0x3f753f35,0xbf463e48,0xbdc9bf6d,0x3f623f55,0xbef1bf80,0x3f7f3f0e,0xbf223ec4,0xbe95bf7b,0xbf550000,0xbe48bf6d,0x3f7b3f35,0xbf0e3ec4,
0xbf0ebf80,0x3f7b3ec4,0xbe483f35,0xbf55bf6d,0x3f550000,0x3e483f6d,0xbf7bbf35,0x3f0ebec4,0x3f0e3f80,0xbf7bbec4,0x3e48bf35,0x3f553f6d,
0xbf550000,0xbe48bf6d,0x3f7b3f35,0xbf0e3ec4,0xbf0ebf80,0x3f7b3ec4,0xbe483f35,0xbf55bf6d,0x3f550000,0x3e483f6d,0xbf7bbf35,0x3f0ebec4,
0x3f0e3f80,0xbf7bbec4,0x3e48bf35,0x3f553f6d,0x3dc9bf35,0x3f753f55,0xbef13ec4,0xbf46bf7b,0xbf22bf80,0x3f623e48,0x3e953f6d,0xbf7fbf0e,
0xbf7fbf35,0x3e95bf0e,0x3f623f6d,0xbf223e48,0xbf460000,0xbef1bf7b,0x3f753ec4,0x3dc93f55,0xbdc93f35,0xbf75bf55,0x3ef1bec4,0x3f463f7b,
0x3f223f80,0xbf62be48,0xbe95bf6d,0x3f7f3f0e,0x3f7f3f35,0xbe953f0e,0xbf62bf6d,0x3f22be48,0x3f460000,0x3ef13f7b,0xbf75bec4,0xbdc9bf55,
0x3f350000,0x3f353f80,0xbf350000,0xbf35bf80,0x3f350000,0x3f353f80,0xbf350000,0xbf35bf80,0x3f350000,0x3f353f80,0xbf350000,0xbf35bf80,
0x3f350000,0x3f353f80,0xbf350000,0xbf35bf80,0x3f350000,0x3f353f80,0xbf350000,0xbf35bf80,0x3f350000,0x3f353f80,0xbf350000,0xbf35bf80,
0x3f350000,0x3f353f80,0xbf350000,0xbf35bf80,0x3f350000,0x3f353f80,0xbf350000,0xbf35bf80,0xbdc9bf35,0x3f753f0e,0x3ef13f6d,0xbf46be48,
0x3f220000,0x3f623f7b,0xbe953ec4,0xbf7fbf55,0xbf7fbf35,0xbe95bf55,0x3f623ec4,0x3f223f7b,0xbf46bf80,0x3ef1be48,0x3f753f6d,0xbdc93f0e,
0x3dc93f35,0xbf75bf0e,0xbef1bf6d,0x3f463e48,0xbf220000,0xbf62bf7b,0x3e95bec4,0x3f7f3f55,0x3f7f3f35,0x3e953f55,0xbf62bec4,0xbf22bf7b,
0x3f463f80,0xbef13e48,0xbf75bf6d,0x3dc9bf0e,0xbf0e0000,0xbf7bbf6d,0xbe48bf35,0x3f553ec4,0x3f553f80,0xbe483ec4,0xbf7bbf35,0xbf0ebf6d,
0x3f0e0000,0x3f7b3f6d,0x3e483f35,0xbf55bec4,0xbf55bf80,0x3e48bec4,0x3f7b3f35,0x3f0e3f6d,0xbf0e0000,0xbf7bbf6d,0xbe48bf35,0x3f553ec4,
0x3f553f80,0xbe483ec4,0xbf7bbf35,0xbf0ebf6d,0x3f0e0000,0x3f7b3f6d,0x3e483f35,0xbf55bec4,0xbf55bf80,0x3e48bec4,0x3f7b3f35,0x3f0e3f6d,
0xbe95bf35,0x3f223e48,0x3f7f3f6d,0x3ef13f55,0x3f623f80,0x3dc93f0e,0xbf46bec4,0xbf75bf7b,0xbf75bf35,0xbf46bf7b,0x3dc9bec4,0x3f623f0e,
0x3ef10000,0x3f7f3f55,0x3f223f6d,0xbe953e48,0x3e953f35,0xbf22be48,0xbf7fbf6d,0xbef1bf55,0xbf62bf80,0xbdc9bf0e,0x3f463ec4,0x3f753f7b,
0x3f753f35,0x3f463f7b,0xbdc93ec4,0xbf62bf0e,0xbef10000,0xbf7fbf55,0xbf22bf6d,0x3e95be48,0x3ec40000,0x3f6d3f35,0x3f6d3f80,0x3ec43f35,
0xbec40000,0xbf6dbf35,0xbf6dbf80,0xbec4bf35,0x3ec40000,0x3f6d3f35,0x3f6d3f80,0x3ec43f35,0xbec40000,0xbf6dbf35,0xbf6dbf80,0xbec4bf35,
0x3ec40000,0x3f6d3f35,0x3f6d3f80,0x3ec43f35,0xbec40000,0xbf6dbf35,0xbf6dbf80,0xbec4bf35,0x3ec40000,0x3f6d3f35,0x3f6d3f80,0x3ec43f35,
0xbec40000,0xbf6dbf35,0xbf6dbf80,0xbec4bf35,0xbef1bf35,0x3dc9be48,0x3f223ec4,0x3f753f55,0xbe950000,0xbf46bf0e,0xbf7fbf6d,0xbf62bf7b,
0xbf62bf35,0xbf7fbf7b,0xbf46bf6d,0xbe95bf0e,0x3f753f80,0x3f223f55,0x3dc93ec4,0xbef1be48,0x3ef13f35,0xbdc93e48,0xbf22bec4,0xbf75bf55,
0x3e950000,0x3f463f0e,0x3f7f3f6d,0x3f623f7b,0x3f623f35,0x3f7f3f7b,0x3f463f6d,0x3e953f0e,0xbf75bf80,0xbf22bf55,0xbdc9bec4,0x3ef13e48,
0xbe480000,0xbf0ebec4,0xbf55bf35,0xbf7bbf6d,0xbf7bbf80,0xbf55bf6d,0xbf0ebf35,0xbe48bec4,0x3e480000,0x3f0e3ec4,0x3f553f35,0x3f7b3f6d,
0x3f7b3f80,0x3f553f6d,0x3f0e3f35,0x3e483ec4,0xbe480000,0xbf0ebec4,0xbf55bf35,0xbf7bbf6d,0xbf7bbf80,0xbf55bf6d,0xbf0ebf35,0xbe48bec4,
0x3e480000,0x3f0e3ec4,0x3f553f35,0x3f7b3f6d,0x3f7b3f80,0x3f553f6d,0x3f0e3f35,0x3e483ec4,0xbf22bf35,0xbef1bf0e,0xbe95bec4,0xbdc9be48,
0xbf7fbf80,0xbf75bf7b,0xbf62bf6d,0xbf46bf55,0xbf46bf35,0xbf62bf55,0xbf75bf6d,0xbf7fbf7b,0xbdc90000,0xbe95be48,0xbef1bec4,0xbf22bf0e,
0x3f223f35,0x3ef13f0e,0x3e953ec4,0x3dc93e48,0x3f7f3f80,0x3f753f7b,0x3f623f6d,0x3f463f55,0x3f463f35,0x3f623f55,0x3f753f6d,0x3f7f3f7b,
0x3dc90000,0x3e953e48,0x3ef13ec4,0x3f223f0e,
};
__device__ __align__(128) const uint32_t T_Gf[4096] = {
0x3f803f80,0x3f803f80,0x3f803f80,0x3f803f80,0x3f803f80,0x3f803f80,0x3f803f80,0x3f803f80,0x3f803f80,0x3f803f80,0x3f803f80,0x3f803f80,
0x3f803f80,0x3f803f80,0x3f803f80,0x3f803f80,0x3f803f80,0x3f803f80,0x3f803f80,0x3f803f80,0x3f803f80,0x3f803f80,0x3f803f80,0x3f803f80,
0x3f803f80,0x3f803f80,0x3f803f80,0x3f803f80,0x3f803f80,0x3f803f80,0x3f803f80,0x3f803f80,0x3f223f35,0x3ef13f0e,0x3e953ec4,0x3dc93e48,
0x3f7f3f80,0x3f753f7b,0x3f623f6d,0x3f463f55,0xbf46bf35,0xbf62bf55,0xbf75bf6d,0xbf7fbf7b,0xbdc90000,0xbe95be48,0xbef1bec4,0xbf22bf0e,
0xbf22bf35,0xbef1bf0e,0xbe95bec4,0xbdc9be48,0xbf7fbf80,0xbf75bf7b,0xbf62bf6d,0xbf46bf55,0x3f463f35,0x3f623f55,0x3f753f6d,0x3f7f3f7b,
0x3dc90000,0x3e953e48,0x3ef13ec4,0x3f223f0e,0xbf7bbf80,0xbf55bf6d,0xbf0ebf35,0xbe48bec4,0x3e480000,0x3f0e3ec4,0x3f553f35,0x3f7b3f6d,
0x3f7b3f80,0x3f553f6d,0x3f0e3f35,0x3e483ec4,0xbe480000,0xbf0ebec4,0xbf55bf35,0xbf7bbf6d,0xbf7bbf80,0xbf55bf6d,0xbf0ebf35,0xbe48bec4,
0x3e480000,0x3f0e3ec4,0x3f553f35,0x3f7b3f6d,0x3f7b3f80,0x3f553f6d,0x3f0e3f35,0x3e483ec4,0xbe480000,0xbf0ebec4,0xbf55bf35,0xbf7bbf6d,
0x3ef13f35,0xbdc93e48,0xbf22bec4,0xbf75bf55,0x3e950000,0x3f463f0e,0x3f7f3f6d,0x3f623f7b,0xbf62bf35,0xbf7fbf7b,0xbf46bf6d,0xbe95bf0e,
0x3f753f80,0x3f223f55,0x3dc93ec4,0xbef1be48,0xbef1bf35,0x3dc9be48,0x3f223ec4,0x3f753f55,0xbe950000,0xbf46bf0e,0xbf7fbf6d,0xbf62bf7b,
0x3f623f35,0x3f7f3f7b,0x3f463f6d,0x3e953f0e,0xbf75bf80,0xbf22bf55,0xbdc9bec4,0x3ef13e48,0x3f6d3f80,0x3ec43f35,0xbec40000,0xbf6dbf35,
0xbf6dbf80,0xbec4bf35,0x3ec40000,0x3f6d3f35,0x3f6d3f80,0x3ec43f35,0xbec40000,0xbf6dbf35,0xbf6dbf80,0xbec4bf35,0x3ec40000,0x3f6d3f35,
0x3f6d3f80,0x3ec43f35,0xbec40000,0xbf6dbf35,0xbf6dbf80,0xbec4bf35,0x3ec40000,0x3f6d3f35,0x3f6d3f80,0x3ec43f35,0xbec40000,0xbf6dbf35,
0xbf6dbf80,0xbec4bf35,0x3ec40000,0x3f6d3f35,0x3e953f35,0xbf22be48,0xbf7fbf6d,0xbef1bf55,0xbf62bf80,0xbdc9bf0e,0x3f463ec4,0x3f753f7b,
0xbf75bf35,0xbf46bf7b,0x3dc9bec4,0x3f623f0e,0x3ef10000,0x3f7f3f55,0x3f223f6d,0xbe953e48,0xbe95bf35,0x3f223e48,0x3f7f3f6d,0x3ef13f55,
0x3f623f80,0x3dc93f0e,0xbf46bec4,0xbf75bf7b,0x3f753f35,0x3f463f7b,0xbdc93ec4,0xbf62bf0e,0xbef10000,0xbf7fbf55,0xbf22bf6d,0x3e95be48,
0xbf55bf80,0x3e48bec4,0x3f7b3f35,0x3f0e3f6d,0xbf0e0000,0xbf7bbf6d,0xbe48bf35,0x3f553ec4,0x3f553f80,0xbe483ec4,0xbf7bbf35,0xbf0ebf6d,
0x3f0e0000,0x3f7b3f6d,0x3e483f35,0xbf55bec4,0xbf55bf80,0x3e48bec4,0x3f7b3f35,0x3f0e3f6d,0xbf0e0000,0xbf7bbf6d,0xbe48bf35,0x3f553ec4,
0x3f553f80,0xbe483ec4,0xbf7bbf35,0xbf0ebf6d,0x3f0e0000,0x3f7b3f6d,0x3e483f35,0xbf55bec4,0x3dc93f35,0xbf75bf0e,0xbef1bf6d,0x3f463e48,
0xbf220000,0xbf62bf7b,0x3e95bec4,0x3f7f3f55,0xbf7fbf35,0xbe95bf55,0x3f623ec4,0x3f223f7b,0xbf46bf80,0x3ef1be48,0x3f753f6d,0xbdc93f0e,
0xbdc9bf35,0x3f753f0e,0x3ef13f6d,0xbf46be48,0x3f220000,0x3f623f7b,0xbe953ec4,0xbf7fbf55,0x3f7f3f35,0x3e953f55,0xbf62bec4,0xbf22bf7b,
0x3f463f80,0xbef13e48,0xbf75bf6d,0x3dc9bf0e,0x3f353f80,0xbf350000,0xbf35bf80,0x3f350000,0x3f353f80,0xbf350000,0xbf35bf80,0x3f350000,
0x3f353f80,0xbf350000,0xbf35bf80,0x3f350000,0x3f353f80,0xbf350000,0xbf35bf80,0x3f350000,0x3f353f80,0xbf350000,0xbf35bf80,0x3f350000,
0x3f353f80,0xbf350000,0xbf35bf80,0x3f350000,0x3f353f80,0xbf350000,0xbf35bf80,0x3f350000,0x3f353f80,0xbf350000,0xbf35bf80,0x3f350000,
0xbdc93f35,0xbf75bf55,0x3ef1bec4,0x3f463f7b,0x3f223f80,0xbf62be48,0xbe95bf6d,0x3f7f3f0e,0xbf7fbf35,0x3e95bf0e,0x3f623f6d,0xbf223e48,
0xbf460000,0xbef1bf7b,0x3f753ec4,0x3dc93f55,0x3dc9bf35,0x3f753f55,0xbef13ec4,0xbf46bf7b,0xbf22bf80,0x3f623e48,0x3e953f6d,0xbf7fbf0e,
0x3f7f3f35,0xbe953f0e,0xbf62bf6d,0x3f22be48,0x3f460000,0x3ef13f7b,0xbf75bec4,0xbdc9bf55,0xbf0ebf80,0x3f7b3ec4,0xbe483f35,0xbf55bf6d,
0x3f550000,0x3e483f6d,0xbf7bbf35,0x3f0ebec4,0x3f0e3f80,0xbf7bbec4,0x3e48bf35,0x3f553f6d,0xbf550000,0xbe48bf6d,0x3f7b3f35,0xbf0e3ec4,
0xbf0ebf80,0x3f7b3ec4,0xbe483f35,0xbf55bf6d,0x3f550000,0x3e483f6d,0xbf7bbf35,0x3f0ebec4,0x3f0e3f80,0xbf7bbec4,0x3e48bf35,0x3f553f6d,
0xbf550000,0xbe48bf6d,0x3f7b3f35,0xbf0e3ec4,0xbe953f35,0xbf22bf7b,0x3f7f3ec4,0xbef13f0e,0x3f620000,0xbdc93f55,0xbf46bf6d,0x3f753e48,
0xbf75bf35,0x3f46be48,0x3dc93f6d,0xbf62bf55,0x3ef13f80,0xbf7fbf0e,0x3f22bec4,0x3e953f7b,0x3e95bf35,0x3f223f7b,0xbf7fbec4,0x3ef1bf0e,
0xbf620000,0x3dc9bf55,0x3f463f6d,0xbf75be48,0x3f753f35,0xbf463e48,0xbdc9bf6d,0x3f623f55,0xbef1bf80,0x3f7f3f0e,0xbf223ec4,0xbe95bf7b,
0x3ec43f80,0xbf6dbf35,0x3f6d0000,0xbec43f35,0xbec4bf80,0x3f6d3f35,0xbf6d0000,0x3ec4bf35,0x3ec43f80,0xbf6dbf35,0x3f6d0000,0xbec43f35,
0xbec4bf80,0x3f6d3f35,0xbf6d0000,0x3ec4bf35,0x3ec43f80,0xbf6dbf35,0x3f6d0000,0xbec43f35,0xbec4bf80,0x3f6d3f35,0xbf6d0000,0x3ec4bf35,
0x3ec43f80,0xbf6dbf35,0x3f6d0000,0xbec43f35,0xbec4bf80,0x3f6d3f35,0xbf6d0000,0x3ec4bf35,0xbef13f35,0xbdc9bf7b,0x3f223f6d,0xbf75bf0e,
0xbe95bf80,0x3f463f55,0xbf7fbec4,0x3f62be48,0xbf62bf35,0x3f7f3e48,0xbf463ec4,0x3e95bf55,0x3f750000,0xbf223f0e,0x3dc9bf6d,0x3ef13f7b,
0x3ef1bf35,0x3dc93f7b,0xbf22bf6d,0x3f753f0e,0x3e953f80,0xbf46bf55,0x3f7f3ec4,0xbf623e48,0x3f623f35,0xbf7fbe48,0x3f46bec4,0xbe953f55,
0xbf750000,0x3f22bf0e,0xbdc93f6d,0xbef1bf7b,0xbe48bf80,0x3f0e3f6d,0xbf55bf35,0x3f7b3ec4,0xbf7b0000,0x3f55bec4,0xbf0e3f35,0x3e48bf6d,
0x3e483f80,0xbf0ebf6d,0x3f553f35,0xbf7bbec4,0x3f7b0000,0xbf553ec4,0x3f0ebf35,0xbe483f6d,0xbe48bf80,0x3f0e3f6d,0xbf55bf35,0x3f7b3ec4,
0xbf7b0000,0x3f55bec4,0xbf0e3f35,0x3e48bf6d,0x3e483f80,0xbf0ebf6d,0x3f553f35,0xbf7bbec4,0x3f7b0000,0xbf553ec4,0x3f0ebf35,0xbe483f6d,
0xbf223f35,0x3ef1bf55,0xbe953f6d,0x3dc9bf7b,0xbf7f0000,0x3f75be48,0xbf623ec4,0x3f46bf0e,0xbf46bf35,0x3f623f0e,0xbf75bec4,0x3f7f3e48,
0xbdc9bf80,0x3e953f7b,0xbef1bf6d,0x3f223f55,0x3f22bf35,0xbef13f55,0x3e95bf6d,0xbdc93f7b,0x3f7f0000,0xbf753e48,0x3f62bec4,0xbf463f0e,
0x3f463f35,0xbf62bf0e,0x3f753ec4,0xbf7fbe48,0x3dc93f80,0xbe95bf7b,0x3ef13f6d,0xbf22bf55,0x3f80,0xbf80,0x3f80,0xbf80,
0x3f80,0xbf80,0x3f80,0xbf80,0x3f80,0xbf80,0x3f80,0xbf80,0x3f80,0xbf80,0x3f80,0xbf80,
0x3f80,0xbf80,0x3f80,0xbf80,0x3f80,0xbf80,0x3f80,0xbf80,0x3f80,0xbf80,0x3f80,0xbf80,
0x3f80,0xbf80,0x3f80,0xbf80,0xbf463f35,0x3f62bf0e,0xbf753ec4,0x3f7fbe48,0xbdc93f80,0x3e95bf7b,0xbef13f6d,0x3f22bf55,
0xbf22bf35,0x3ef13f55,0xbe95bf6d,0x3dc93f7b,0xbf7f0000,0x3f753e48,0xbf62bec4,0x3f463f0e,0x3f46bf35,0xbf623f0e,0x3f75bec4,0xbf7f3e48,
0x3dc9bf80,0xbe953f7b,0x3ef1bf6d,0xbf223f55,0x3f223f35,0xbef1bf55,0x3e953f6d,0xbdc9bf7b,0x3f7f0000,0xbf75be48,0x3f623ec4,0xbf46bf0e,
0x3e48bf80,0xbf0e3f6d,0x3f55bf35,0xbf7b3ec4,0x3f7b0000,0xbf55bec4,0x3f0e3f35,0xbe48bf6d,0xbe483f80,0x3f0ebf6d,0xbf553f35,0x3f7bbec4,
0xbf7b0000,0x3f553ec4,0xbf0ebf35,0x3e483f6d,0x3e48bf80,0xbf0e3f6d,0x3f55bf35,0xbf7b3ec4,0x3f7b0000,0xbf55bec4,0x3f0e3f35,0xbe48bf6d,
0xbe483f80,0x3f0ebf6d,0xbf553f35,0x3f7bbec4,0xbf7b0000,0x3f553ec4,0xbf0ebf35,0x3e483f6d,0xbf623f35,0x3f7fbe48,0xbf46bec4,0x3e953f55,
0x3f750000,0xbf22bf0e,0x3dc93f6d,0x3ef1bf7b,0xbef1bf35,0xbdc93f7b,0x3f22bf6d,0xbf753f0e,0xbe953f80,0x3f46bf55,0xbf7f3ec4,0x3f623e48,
0x3f62bf35,0xbf7f3e48,0x3f463ec4,0xbe95bf55,0xbf750000,0x3f223f0e,0xbdc9bf6d,0xbef13f7b,0x3ef13f35,0x3dc9bf7b,0xbf223f6d,0x3f75bf0e,
0x3e95bf80,0xbf463f55,0x3f7fbec4,0xbf62be48,0xbec43f80,0x3f6dbf35,0xbf6d0000,0x3ec43f35,0x3ec4bf80,0xbf6d3f35,0x3f6d0000,0xbec4bf35,
0xbec43f80,0x3f6dbf35,0xbf6d0000,0x3ec43f35,0x3ec4bf80,0xbf6d3f35,0x3f6d0000,0xbec4bf35,0xbec43f80,0x3f6dbf35,0xbf6d0000,0x3ec43f35,
0x3ec4bf80,0xbf6d3f35,0x3f6d0000,0xbec4bf35,0xbec43f80,0x3f6dbf35,0xbf6d0000,0x3ec43f35,0x3ec4bf80,0xbf6d3f35,0x3f6d0000,0xbec4bf35,
0xbf753f35,0x3f463e48,0x3dc9bf6d,0xbf623f55,0x3ef1bf80,0xbf7f3f0e,0x3f223ec4,0x3e95bf7b,0xbe95bf35,0xbf223f7b,0x3f7fbec4,0xbef1bf0e,
0x3f620000,0xbdc9bf55,0xbf463f6d,0x3f75be48,0x3f75bf35,0xbf46be48,0xbdc93f6d,0x3f62bf55,0xbef13f80,0x3f7fbf0e,0xbf22bec4,0xbe953f7b,
0x3e953f35,0x3f22bf7b,0xbf7f3ec4,0x3ef13f0e,0xbf620000,0x3dc93f55,0x3f46bf6d,0xbf753e48,0x3f0ebf80,0xbf7b3ec4,0x3e483f35,0x3f55bf6d,
0xbf550000,0xbe483f6d,0x3f7bbf35,0xbf0ebec4,0xbf0e3f80,0x3f7bbec4,0xbe48bf35,0xbf553f6d,0x3f550000,0x3e48bf6d,0xbf7b3f35,0x3f0e3ec4,
0x3f0ebf80,0xbf7b3ec4,0x3e483f35,0x3f55bf6d,0xbf550000,0xbe483f6d,0x3f7bbf35,0xbf0ebec4,0xbf0e3f80,0x3f7bbec4,0xbe48bf35,0xbf553f6d,
0x3f550000,0x3e48bf6d,0xbf7b3f35,0x3f0e3ec4,0xbf7f3f35,0x3e953f0e,0x3f62bf6d,0xbf22be48,0xbf460000,0xbef13f7b,0x3f75bec4,0x3dc9bf55,
0xbdc9bf35,0xbf753f55,0x3ef13ec4,0x3f46bf7b,0x3f22bf80,0xbf623e48,0xbe953f6d,0x3f7fbf0e,0x3f7fbf35,0xbe95bf0e,0xbf623f6d,0x3f223e48,
0x3f460000,0x3ef1bf7b,0xbf753ec4,0xbdc93f55,0x3dc93f35,0x3f75bf55,0xbef1bec4,0xbf463f7b,0xbf223f80,0x3f62be48,0x3e95bf6d,0xbf7f3f0e,
0xbf353f80,0x3f350000,0x3f35bf80,0xbf350000,0xbf353f80,0x3f350000,0x3f35bf80,0xbf350000,0xbf353f80,0x3f350000,0x3f35bf80,0xbf350000,
0xbf353f80,0x3f350000,0x3f35bf80,0xbf350000,0xbf353f80,0x3f350000,0x3f35bf80,0xbf350000,0xbf353f80,0x3f350000,0x3f35bf80,0xbf350000,
0xbf353f80,0x3f350000,0x3f35bf80,0xbf350000,0xbf353f80,0x3f350000,0x3f35bf80,0xbf350000,0xbf7f3f35,0xbe953f55,0x3f62bec4,0x3f22bf7b,
0xbf463f80,0x3ef13e48,0x3f75bf6d,0xbdc9bf0e,0x3dc9bf35,0xbf753f0e,0xbef13f6d,0x3f46be48,0xbf220000,0xbf623f7b,0x3e953ec4,0x3f7fbf55,
0x3f7fbf35,0x3e95bf55,0xbf623ec4,0xbf223f7b,0x3f46bf80,0xbef1be48,0xbf753f6d,0x3dc93f0e,0xbdc93f35,0x3f75bf0e,0x3ef1bf6d,0xbf463e48,
0x3f220000,0x3f62bf7b,0xbe95bec4,0xbf7f3f55,0x3f55bf80,0xbe48bec4,0xbf7b3f35,0xbf0e3f6d,0x3f0e0000,0x3f7bbf6d,0x3e48bf35,0xbf553ec4,
0xbf553f80,0x3e483ec4,0x3f7bbf35,0x3f0ebf6d,0xbf0e0000,0xbf7b3f6d,0xbe483f35,0x3f55bec4,0x3f55bf80,0xbe48bec4,0xbf7b3f35,0xbf0e3f6d,
0x3f0e0000,0x3f7bbf6d,0x3e48bf35,0xbf553ec4,0xbf553f80,0x3e483ec4,0x3f7bbf35,0x3f0ebf6d,0xbf0e0000,0xbf7b3f6d,0xbe483f35,0x3f55bec4,
0xbf753f35,0xbf463f7b,0x3dc93ec4,0x3f62bf0e,0x3ef10000,0x3f7fbf55,0x3f22bf6d,0xbe95be48,0x3e95bf35,0xbf223e48,0xbf7f3f6d,0xbef13f55,
0xbf623f80,0xbdc93f0e,0x3f46bec4,0x3f75bf7b,0x3f75bf35,0x3f46bf7b,0xbdc9bec4,0xbf623f0e,0xbef10000,0xbf7f3f55,0xbf223f6d,0x3e953e48,
0xbe953f35,0x3f22be48,0x3f7fbf6d,0x3ef1bf55,0x3f62bf80,0x3dc9bf0e,0xbf463ec4,0xbf753f7b,0xbf6d3f80,0xbec43f35,0x3ec40000,0x3f6dbf35,
0x3f6dbf80,0x3ec4bf35,0xbec40000,0xbf6d3f35,0xbf6d3f80,0xbec43f35,0x3ec40000,0x3f6dbf35,0x3f6dbf80,0x3ec4bf35,0xbec40000,0xbf6d3f35,
0xbf6d3f80,0xbec43f35,0x3ec40000,0x3f6dbf35,0x3f6dbf80,0x3ec4bf35,0xbec40000,0xbf6d3f35,0xbf6d3f80,0xbec43f35,0x3ec40000,0x3f6dbf35,
0x3f6dbf80,0x3ec4bf35,0xbec40000,0xbf6d3f35,0xbf623f35,0xbf7f3f7b,0xbf463f6d,0xbe953f0e,0x3f75bf80,0x3f22bf55,0x3dc9bec4,0xbef13e48,
0x3ef1bf35,0xbdc9be48,0xbf223ec4,0xbf753f55,0x3e950000,0x3f46bf0e,0x3f7fbf6d,0x3f62bf7b,0x3f62bf35,0x3f7fbf7b,0x3f46bf6d,0x3e95bf0e,
0xbf753f80,0xbf223f55,0xbdc93ec4,0x3ef1be48,0xbef13f35,0x3dc93e48,0x3f22bec4,0x3f75bf55,0xbe950000,0xbf463f0e,0xbf7f3f6d,0xbf623f7b,
0x3f7bbf80,0x3f55bf6d,0x3f0ebf35,0x3e48bec4,0xbe480000,0xbf0e3ec4,0xbf553f35,0xbf7b3f6d,0xbf7b3f80,0xbf553f6d,0xbf0e3f35,0xbe483ec4,
0x3e480000,0x3f0ebec4,0x3f55bf35,0x3f7bbf6d,0x3f7bbf80,0x3f55bf6d,0x3f0ebf35,0x3e48bec4,0xbe480000,0xbf0e3ec4,0xbf553f35,0xbf7b3f6d,
0xbf7b3f80,0xbf553f6d,0xbf0e3f35,0xbe483ec4,0x3e480000,0x3f0ebec4,0x3f55bf35,0x3f7bbf6d,0xbf463f35,0xbf623f55,0xbf753f6d,0xbf7f3f7b,
0xbdc90000,0xbe953e48,0xbef13ec4,0xbf223f0e,0x3f22bf35,0x3ef1bf0e,0x3e95bec4,0x3dc9be48,0x3f7fbf80,0x3f75bf7b,0x3f62bf6d,0x3f46bf55,
0x3f46bf35,0x3f62bf55,0x3f75bf6d,0x3f7fbf7b,0x3dc90000,0x3e95be48,0x3ef1bec4,0x3f22bf0e,0xbf223f35,0xbef13f0e,0xbe953ec4,0xbdc93e48,
0xbf7f3f80,0xbf753f7b,0xbf623f6d,0xbf463f55,0xbf803f80,0xbf803f80,0xbf803f80,0xbf803f80,0xbf803f80,0xbf803f80,0xbf803f80,0xbf803f80,
0xbf803f80,0xbf803f80,0xbf803f80,0xbf803f80,0xbf803f80,0xbf803f80,0xbf803f80,0xbf803f80,0xbf803f80,0xbf803f80,0xbf803f80,0xbf803f80,
0xbf803f80,0xbf803f80,0xbf803f80,0xbf803f80,0xbf803f80,0xbf803f80,0xbf803f80,0xbf803f80,0xbf803f80,0xbf803f80,0xbf803f80,0xbf803f80,
0xbf46bf35,0xbf62bf55,0xbf75bf6d,0xbf7fbf7b,0xbdc90000,0xbe95be48,0xbef1bec4,0xbf22bf0e,0xbf22bf35,0xbef1bf0e,0xbe95bec4,0xbdc9be48,
0xbf7fbf80,0xbf75bf7b,0xbf62bf6d,0xbf46bf55,0x3f463f35,0x3f623f55,0x3f753f6d,0x3f7f3f7b,0x3dc90000,0x3e953e48,0x3ef13ec4,0x3f223f0e,
0x3f223f35,0x3ef13f0e,0x3e953ec4,0x3dc93e48,0x3f7f3f80,0x3f753f7b,0x3f623f6d,0x3f463f55,0x3e480000,0x3f0e3ec4,0x3f553f35,0x3f7b3f6d,
0x3f7b3f80,0x3f553f6d,0x3f0e3f35,0x3e483ec4,0xbe480000,0xbf0ebec4,0xbf55bf35,0xbf7bbf6d,0xbf7bbf80,0xbf55bf6d,0xbf0ebf35,0xbe48bec4,
0x3e480000,0x3f0e3ec4,0x3f553f35,0x3f7b3f6d,0x3f7b3f80,0x3f553f6d,0x3f0e3f35,0x3e483ec4,0xbe480000,0xbf0ebec4,0xbf55bf35,0xbf7bbf6d,
0xbf7bbf80,0xbf55bf6d,0xbf0ebf35,0xbe48bec4,0xbf62bf35,0xbf7fbf7b,0xbf46bf6d,0xbe95bf0e,0x3f753f80,0x3f223f55,0x3dc93ec4,0xbef1be48,
0xbef1bf35,0x3dc9be48,0x3f223ec4,0x3f753f55,0xbe950000,0xbf46bf0e,0xbf7fbf6d,0xbf62bf7b,0x3f623f35,0x3f7f3f7b,0x3f463f6d,0x3e953f0e,
0xbf75bf80,0xbf22bf55,0xbdc9bec4,0x3ef13e48,0x3ef13f35,0xbdc93e48,0xbf22bec4,0xbf75bf55,0x3e950000,0x3f463f0e,0x3f7f3f6d,0x3f623f7b,
0xbec40000,0xbf6dbf35,0xbf6dbf80,0xbec4bf35,0x3ec40000,0x3f6d3f35,0x3f6d3f80,0x3ec43f35,0xbec40000,0xbf6dbf35,0xbf6dbf80,0xbec4bf35,
0x3ec40000,0x3f6d3f35,0x3f6d3f80,0x3ec43f35,0xbec40000,0xbf6dbf35,0xbf6dbf80,0xbec4bf35,0x3ec40000,0x3f6d3f35,0x3f6d3f80,0x3ec43f35,
0xbec40000,0xbf6dbf35,0xbf6dbf80,0xbec4bf35,0x3ec40000,0x3f6d3f35,0x3f6d3f80,0x3ec43f35,0xbf75bf35,0xbf46bf7b,0x3dc9bec4,0x3f623f0e,
0x3ef10000,0x3f7f3f55,0x3f223f6d,0xbe953e48,0xbe95bf35,0x3f223e48,0x3f7f3f6d,0x3ef13f55,0x3f623f80,0x3dc93f0e,0xbf46bec4,0xbf75bf7b,
0x3f753f35,0x3f463f7b,0xbdc93ec4,0xbf62bf0e,0xbef10000,0xbf7fbf55,0xbf22bf6d,0x3e95be48,0x3e953f35,0xbf22be48,0xbf7fbf6d,0xbef1bf55,
0xbf62bf80,0xbdc9bf0e,0x3f463ec4,0x3f753f7b,0x3f0e0000,0x3f7b3f6d,0x3e483f35,0xbf55bec4,0xbf55bf80,0x3e48bec4,0x3f7b3f35,0x3f0e3f6d,
0xbf0e0000,0xbf7bbf6d,0xbe48bf35,0x3f553ec4,0x3f553f80,0xbe483ec4,0xbf7bbf35,0xbf0ebf6d,0x3f0e0000,0x3f7b3f6d,0x3e483f35,0xbf55bec4,
0xbf55bf80,0x3e48bec4,0x3f7b3f35,0x3f0e3f6d,0xbf0e0000,0xbf7bbf6d,0xbe48bf35,0x3f553ec4,0x3f553f80,0xbe483ec4,0xbf7bbf35,0xbf0ebf6d,
0xbf7fbf35,0xbe95bf55,0x3f623ec4,0x3f223f7b,0xbf46bf80,0x3ef1be48,0x3f753f6d,0xbdc93f0e,0xbdc9bf35,0x3f753f0e,0x3ef13f6d,0xbf46be48,
0x3f220000,0x3f623f7b,0xbe953ec4,0xbf7fbf55,0x3f7f3f35,0x3e953f55,0xbf62bec4,0xbf22bf7b,0x3f463f80,0xbef13e48,0xbf75bf6d,0x3dc9bf0e,
0x3dc93f35,0xbf75bf0e,0xbef1bf6d,0x3f463e48,0xbf220000,0xbf62bf7b,0x3e95bec4,0x3f7f3f55,0xbf350000,0xbf35bf80,0x3f350000,0x3f353f80,
0xbf350000,0xbf35bf80,0x3f350000,0x3f353f80,0xbf350000,0xbf35bf80,0x3f350000,0x3f353f80,0xbf350000,0xbf35bf80,0x3f350000,0x3f353f80,
0xbf350000,0xbf35bf80,0x3f350000,0x3f353f80,0xbf350000,0xbf35bf80,0x3f350000,0x3f353f80,0xbf350000,0xbf35bf80,0x3f350000,0x3f353f80,
0xbf350000,0xbf35bf80,0x3f350000,0x3f353f80,0xbf7fbf35,0x3e95bf0e,0x3f623f6d,0xbf223e48,0xbf460000,0xbef1bf7b,0x3f753ec4,0x3dc93f55,
0x3dc9bf35,0x3f753f55,0xbef13ec4,0xbf46bf7b,0xbf22bf80,0x3f623e48,0x3e953f6d,0xbf7fbf0e,0x3f7f3f35,0xbe953f0e,0xbf62bf6d,0x3f22be48,
0x3f460000,0x3ef13f7b,0xbf75bec4,0xbdc9bf55,0xbdc93f35,0xbf75bf55,0x3ef1bec4,0x3f463f7b,0x3f223f80,0xbf62be48,0xbe95bf6d,0x3f7f3f0e,
0x3f550000,0x3e483f6d,0xbf7bbf35,0x3f0ebec4,0x3f0e3f80,0xbf7bbec4,0x3e48bf35,0x3f553f6d,0xbf550000,0xbe48bf6d,0x3f7b3f35,0xbf0e3ec4,
0xbf0ebf80,0x3f7b3ec4,0xbe483f35,0xbf55bf6d,0x3f550000,0x3e483f6d,0xbf7bbf35,0x3f0ebec4,0x3f0e3f80,0xbf7bbec4,0x3e48bf35,0x3f553f6d,
0xbf550000,0xbe48bf6d,0x3f7b3f35,0xbf0e3ec4,0xbf0ebf80,0x3f7b3ec4,0xbe483f35,0xbf55bf6d,0xbf75bf35,0x3f46be48,0x3dc93f6d,0xbf62bf55,
0x3ef13f80,0xbf7fbf0e,0x3f22bec4,0x3e953f7b,0x3e95bf35,0x3f223f7b,0xbf7fbec4,0x3ef1bf0e,0xbf620000,0x3dc9bf55,0x3f463f6d,0xbf75be48,
0x3f753f35,0xbf463e48,0xbdc9bf6d,0x3f623f55,0xbef1bf80,0x3f7f3f0e,0xbf223ec4,0xbe95bf7b,0xbe953f35,0xbf22bf7b,0x3f7f3ec4,0xbef13f0e,
0x3f620000,0xbdc93f55,0xbf46bf6d,0x3f753e48,0xbf6d0000,0x3ec4bf35,0x3ec43f80,0xbf6dbf35,0x3f6d0000,0xbec43f35,0xbec4bf80,0x3f6d3f35,
0xbf6d0000,0x3ec4bf35,0x3ec43f80,0xbf6dbf35,0x3f6d0000,0xbec43f35,0xbec4bf80,0x3f6d3f35,0xbf6d0000,0x3ec4bf35,0x3ec43f80,0xbf6dbf35,
0x3f6d0000,0xbec43f35,0xbec4bf80,0x3f6d3f35,0xbf6d0000,0x3ec4bf35,0x3ec43f80,0xbf6dbf35,0x3f6d0000,0xbec43f35,0xbec4bf80,0x3f6d3f35,
0xbf62bf35,0x3f7f3e48,0xbf463ec4,0x3e95bf55,0x3f750000,0xbf223f0e,0x3dc9bf6d,0x3ef13f7b,0x3ef1bf35,0x3dc93f7b,0xbf22bf6d,0x3f753f0e,
0x3e953f80,0xbf46bf55,0x3f7f3ec4,0xbf623e48,0x3f623f35,0xbf7fbe48,0x3f46bec4,0xbe953f55,0xbf750000,0x3f22bf0e,0xbdc93f6d,0xbef1bf7b,
0xbef13f35,0xbdc9bf7b,0x3f223f6d,0xbf75bf0e,0xbe95bf80,0x3f463f55,0xbf7fbec4,0x3f62be48,0x3f7b0000,0xbf553ec4,0x3f0ebf35,0xbe483f6d,
0xbe48bf80,0x3f0e3f6d,0xbf55bf35,0x3f7b3ec4,0xbf7b0000,0x3f55bec4,0xbf0e3f35,0x3e48bf6d,0x3e483f80,0xbf0ebf6d,0x3f553f35,0xbf7bbec4,
0x3f7b0000,0xbf553ec4,0x3f0ebf35,0xbe483f6d,0xbe48bf80,0x3f0e3f6d,0xbf55bf35,0x3f7b3ec4,0xbf7b0000,0x3f55bec4,0xbf0e3f35,0x3e48bf6d,
0x3e483f80,0xbf0ebf6d,0x3f553f35,0xbf7bbec4,0xbf46bf35,0x3f623f0e,0xbf75bec4,0x3f7f3e48,0xbdc9bf80,0x3e953f7b,0xbef1bf6d,0x3f223f55,
0x3f22bf35,0xbef13f55,0x3e95bf6d,0xbdc93f7b,0x3f7f0000,0xbf753e48,0x3f62bec4,0xbf463f0e,0x3f463f35,0xbf62bf0e,0x3f753ec4,0xbf7fbe48,
0x3dc93f80,0xbe95bf7b,0x3ef13f6d,0xbf22bf55,0xbf223f35,0x3ef1bf55,0xbe953f6d,0x3dc9bf7b,0xbf7f0000,0x3f75be48,0xbf623ec4,0x3f46bf0e,
0xbf800000,0x3f800000,0xbf800000,0x3f800000,0xbf800000,0x3f800000,0xbf800000,0x3f800000,0xbf800000,0x3f800000,0xbf800000,0x3f800000,
0xbf800000,0x3f800000,0xbf800000,0x3f800000,0xbf800000,0x3f800000,0xbf800000,0x3f800000,0xbf800000,0x3f800000,0xbf800000,0x3f800000,
0xbf800000,0x3f800000,0xbf800000,0x3f800000,0xbf800000,0x3f800000,0xbf800000,0x3f800000,0xbf22bf35,0x3ef13f55,0xbe95bf6d,0x3dc93f7b,
0xbf7f0000,0x3f753e48,0xbf62bec4,0x3f463f0e,0x3f46bf35,0xbf623f0e,0x3f75bec4,0xbf7f3e48,0x3dc9bf80,0xbe953f7b,0x3ef1bf6d,0xbf223f55,
0x3f223f35,0xbef1bf55,0x3e953f6d,0xbdc9bf7b,0x3f7f0000,0xbf75be48,0x3f623ec4,0xbf46bf0e,0xbf463f35,0x3f62bf0e,0xbf753ec4,0x3f7fbe48,
0xbdc93f80,0x3e95bf7b,0xbef13f6d,0x3f22bf55,0x3f7b0000,0xbf55bec4,0x3f0e3f35,0xbe48bf6d,0xbe483f80,0x3f0ebf6d,0xbf553f35,0x3f7bbec4,
0xbf7b0000,0x3f553ec4,0xbf0ebf35,0x3e483f6d,0x3e48bf80,0xbf0e3f6d,0x3f55bf35,0xbf7b3ec4,0x3f7b0000,0xbf55bec4,0x3f0e3f35,0xbe48bf6d,
0xbe483f80,0x3f0ebf6d,0xbf553f35,0x3f7bbec4,0xbf7b0000,0x3f553ec4,0xbf0ebf35,0x3e483f6d,0x3e48bf80,0xbf0e3f6d,0x3f55bf35,0xbf7b3ec4,
0xbef1bf35,0xbdc93f7b,0x3f22bf6d,0xbf753f0e,0xbe953f80,0x3f46bf55,0xbf7f3ec4,0x3f623e48,0x3f62bf35,0xbf7f3e48,0x3f463ec4,0xbe95bf55,
0xbf750000,0x3f223f0e,0xbdc9bf6d,0xbef13f7b,0x3ef13f35,0x3dc9bf7b,0xbf223f6d,0x3f75bf0e,0x3e95bf80,0xbf463f55,0x3f7fbec4,0xbf62be48,
0xbf623f35,0x3f7fbe48,0xbf46bec4,0x3e953f55,0x3f750000,0xbf22bf0e,0x3dc93f6d,0x3ef1bf7b,0xbf6d0000,0x3ec43f35,0x3ec4bf80,0xbf6d3f35,
0x3f6d0000,0xbec4bf35,0xbec43f80,0x3f6dbf35,0xbf6d0000,0x3ec43f35,0x3ec4bf80,0xbf6d3f35,0x3f6d0000,0xbec4bf35,0xbec43f80,0x3f6dbf35,
0xbf6d0000,0x3ec43f35,0x3ec4bf80,0xbf6d3f35,0x3f6d0000,0xbec4bf35,0xbec43f80,0x3f6dbf35,0xbf6d0000,0x3ec43f35,0x3ec4bf80,0xbf6d3f35,
0x3f6d0000,0xbec4bf35,0xbec43f80,0x3f6dbf35,0xbe95bf35,0xbf223f7b,0x3f7fbec4,0xbef1bf0e,0x3f620000,0xbdc9bf55,0xbf463f6d,0x3f75be48,
0x3f75bf35,0xbf46be48,0xbdc93f6d,0x3f62bf55,0xbef13f80,0x3f7fbf0e,0xbf22bec4,0xbe953f7b,0x3e953f35,0x3f22bf7b,0xbf7f3ec4,0x3ef13f0e,
0xbf620000,0x3dc93f55,0x3f46bf6d,0xbf753e48,0xbf753f35,0x3f463e48,0x3dc9bf6d,0xbf623f55,0x3ef1bf80,0xbf7f3f0e,0x3f223ec4,0x3e95bf7b,
0x3f550000,0x3e48bf6d,0xbf7b3f35,0x3f0e3ec4,0x3f0ebf80,0xbf7b3ec4,0x3e483f35,0x3f55bf6d,0xbf550000,0xbe483f6d,0x3f7bbf35,0xbf0ebec4,
0xbf0e3f80,0x3f7bbec4,0xbe48bf35,0xbf553f6d,0x3f550000,0x3e48bf6d,0xbf7b3f35,0x3f0e3ec4,0x3f0ebf80,0xbf7b3ec4,0x3e483f35,0x3f55bf6d,
0xbf550000,0xbe483f6d,0x3f7bbf35,0xbf0ebec4,0xbf0e3f80,0x3f7bbec4,0xbe48bf35,0xbf553f6d,0xbdc9bf35,0xbf753f55,0x3ef13ec4,0x3f46bf7b,
0x3f22bf80,0xbf623e48,0xbe953f6d,0x3f7fbf0e,0x3f7fbf35,0xbe95bf0e,0xbf623f6d,0x3f223e48,0x3f460000,0x3ef1bf7b,0xbf753ec4,0xbdc93f55,
0x3dc93f35,0x3f75bf55,0xbef1bec4,0xbf463f7b,0xbf223f80,0x3f62be48,0x3e95bf6d,0xbf7f3f0e,0xbf7f3f35,0x3e953f0e,0x3f62bf6d,0xbf22be48,
0xbf460000,0xbef13f7b,0x3f75bec4,0x3dc9bf55,0xbf350000,0xbf353f80,0x3f350000,0x3f35bf80,0xbf350000,0xbf353f80,0x3f350000,0x3f35bf80,
0xbf350000,0xbf353f80,0x3f350000,0x3f35bf80,0xbf350000,0xbf353f80,0x3f350000,0x3f35bf80,0xbf350000,0xbf353f80,0x3f350000,0x3f35bf80,
0xbf350000,0xbf353f80,0x3f350000,0x3f35bf80,0xbf350000,0xbf353f80,0x3f350000,0x3f35bf80,0xbf350000,0xbf353f80,0x3f350000,0x3f35bf80,
0x3dc9bf35,0xbf753f0e,0xbef13f6d,0x3f46be48,0xbf220000,0xbf623f7b,0x3e953ec4,0x3f7fbf55,0x3f7fbf35,0x3e95bf55,0xbf623ec4,0xbf223f7b,
0x3f46bf80,0xbef1be48,0xbf753f6d,0x3dc93f0e,0xbdc93f35,0x3f75bf0e,0x3ef1bf6d,0xbf463e48,0x3f220000,0x3f62bf7b,0xbe95bec4,0xbf7f3f55,
0xbf7f3f35,0xbe953f55,0x3f62bec4,0x3f22bf7b,0xbf463f80,0x3ef13e48,0x3f75bf6d,0xbdc9bf0e,0x3f0e0000,0x3f7bbf6d,0x3e48bf35,0xbf553ec4,
0xbf553f80,0x3e483ec4,0x3f7bbf35,0x3f0ebf6d,0xbf0e0000,0xbf7b3f6d,0xbe483f35,0x3f55bec4,0x3f55bf80,0xbe48bec4,0xbf7b3f35,0xbf0e3f6d,
0x3f0e0000,0x3f7bbf6d,0x3e48bf35,0xbf553ec4,0xbf553f80,0x3e483ec4,0x3f7bbf35,0x3f0ebf6d,0xbf0e0000,0xbf7b3f6d,0xbe483f35,0x3f55bec4,
0x3f55bf80,0xbe48bec4,0xbf7b3f35,0xbf0e3f6d,0x3e95bf35,0xbf223e48,0xbf7f3f6d,0xbef13f55,0xbf623f80,0xbdc93f0e,0x3f46bec4,0x3f75bf7b,
0x3f75bf35,0x3f46bf7b,0xbdc9bec4,0xbf623f0e,0xbef10000,0xbf7f3f55,0xbf223f6d,0x3e953e48,0xbe953f35,0x3f22be48,0x3f7fbf6d,0x3ef1bf55,
0x3f62bf80,0x3dc9bf0e,0xbf463ec4,0xbf753f7b,0xbf753f35,0xbf463f7b,0x3dc93ec4,0x3f62bf0e,0x3ef10000,0x3f7fbf55,0x3f22bf6d,0xbe95be48,
0xbec40000,0xbf6d3f35,0xbf6d3f80,0xbec43f35,0x3ec40000,0x3f6dbf35,0x3f6dbf80,0x3ec4bf35,0xbec40000,0xbf6d3f35,0xbf6d3f80,0xbec43f35,
0x3ec40000,0x3f6dbf35,0x3f6dbf80,0x3ec4bf35,0xbec40000,0xbf6d3f35,0xbf6d3f80,0xbec43f35,0x3ec40000,0x3f6dbf35,0x3f6dbf80,0x3ec4bf35,
0xbec40000,0xbf6d3f35,0xbf6d3f80,0xbec43f35,0x3ec40000,0x3f6dbf35,0x3f6dbf80,0x3ec4bf35,0x3ef1bf35,0xbdc9be48,0xbf223ec4,0xbf753f55,
0x3e950000,0x3f46bf0e,0x3f7fbf6d,0x3f62bf7b,0x3f62bf35,0x3f7fbf7b,0x3f46bf6d,0x3e95bf0e,0xbf753f80,0xbf223f55,0xbdc93ec4,0x3ef1be48,
0xbef13f35,0x3dc93e48,0x3f22bec4,0x3f75bf55,0xbe950000,0xbf463f0e,0xbf7f3f6d,0xbf623f7b,0xbf623f35,0xbf7f3f7b,0xbf463f6d,0xbe953f0e,
0x3f75bf80,0x3f22bf55,0x3dc9bec4,0xbef13e48,0x3e480000,0x3f0ebec4,0x3f55bf35,0x3f7bbf6d,0x3f7bbf80,0x3f55bf6d,0x3f0ebf35,0x3e48bec4,
0xbe480000,0xbf0e3ec4,0xbf553f35,0xbf7b3f6d,0xbf7b3f80,0xbf553f6d,0xbf0e3f35,0xbe483ec4,0x3e480000,0x3f0ebec4,0x3f55bf35,0x3f7bbf6d,
0x3f7bbf80,0x3f55bf6d,0x3f0ebf35,0x3e48bec4,0xbe480000,0xbf0e3ec4,0xbf553f35,0xbf7b3f6d,0xbf7b3f80,0xbf553f6d,0xbf0e3f35,0xbe483ec4,
0x3f22bf35,0x3ef1bf0e,0x3e95bec4,0x3dc9be48,0x3f7fbf80,0x3f75bf7b,0x3f62bf6d,0x3f46bf55,0x3f46bf35,0x3f62bf55,0x3f75bf6d,0x3f7fbf7b,
0x3dc90000,0x3e95be48,0x3ef1bec4,0x3f22bf0e,0xbf223f35,0xbef13f0e,0xbe953ec4,0xbdc93e48,0xbf7f3f80,0xbf753f7b,0xbf623f6d,0xbf463f55,
0xbf463f35,0xbf623f55,0xbf753f6d,0xbf7f3f7b,0xbdc90000,0xbe953e48,0xbef13ec4,0xbf223f0e,0x3f803f80,0x3f7d3f7f,0x3f783f7b,0x3f713f75,
0x3f673f6d,0x3f5c3f62,0x3f4e3f55,0x3f3e3f46,0x3f2c3f35,0x3f183f22,0x3f043f0e,0x3edb3ef1,0x3eac3ec4,0x3e793e95,0x3e163e48,0x3d493dc9,
0xbd490000,0xbe16bdc9,0xbe79be48,0xbeacbe95,0xbedbbec4,0xbf04bef1,0xbf18bf0e,0xbf2cbf22,0xbf3ebf35,0xbf4ebf46,0xbf5cbf55,0xbf67bf62,
0xbf71bf6d,0xbf78bf75,0xbf7dbf7b,0xbf80bf7f,0x3e793ec4,0xbd493dc9,0xbeacbe48,0xbf18bef1,0x3f7d3f80,0x3f673f75,0x3f3e3f55,0x3f043f22,
0xbf5cbf6d,0xbf2cbf46,0xbedbbf0e,0xbe16be95,0xbf4ebf35,0xbf71bf62,0xbf80bf7b,0xbf78bf7f,0x3f783f6d,0x3f803f7f,0x3f713f7b,0x3f4e3f62,
0x3e160000,0x3edb3e95,0x3f2c3f0e,0x3f5c3f46,0xbf04bec4,0xbf3ebf22,0xbf67bf55,0xbf7dbf75,0x3f183f35,0x3eac3ef1,0x3d493e48,0xbe79bdc9,
0xbf04bf35,0xbd49be95,0x3edb3e48,0x3f4e3f22,0x3f7d3f6d,0x3f713f7f,0x3f2c3f55,0x3e793ef1,0x3f783f80,0x3f3e3f62,0x3eac3f0e,0xbe163dc9,
0xbf18bec4,0xbf67bf46,0xbf80bf7b,0xbf5cbf75,0x3f5c3f35,0x3f803f75,0x3f673f7b,0x3f183f46,0x3e163ec4,0xbeacbdc9,0xbf3ebf0e,0xbf78bf62,
0xbe790000,0xbf2cbef1,0xbf71bf55,0xbf7dbf7f,0xbf4ebf6d,0xbedbbf22,0x3d49be48,0x3f043e95,0xbf2cbec4,0xbf7dbf62,0xbf5cbf7b,0xbeacbf22,
0x3f673f35,0x3f783f7f,0x3f183f55,0xbd493e95,0xbf80bf6d,0xbf4ebf75,0xbe79bf0e,0x3edb3dc9,0x3f713f80,0x3f043f46,0xbe163e48,0xbf3ebef1,
0x3f3e3f6d,0x3e163ef1,0xbf04be48,0xbf71bf46,0xbedbbf35,0x3e79bdc9,0x3f4e3f0e,0x3f803f75,0x3d493ec4,0xbf18be95,0xbf78bf55,0xbf67bf7f,
0x3eac0000,0x3f5c3f22,0x3f7d3f7b,0x3f2c3f62,0xbedb0000,0xbf78bf46,0xbf4ebf7b,0xbd49bef1,0x3f3e3ec4,0x3f7d3f75,0x3f043f55,0xbeac3dc9,
0xbf71bf35,0xbf5cbf7f,0xbe16bf0e,0x3f2c3e95,0x3f803f6d,0x3f183f62,0xbe793e48,0xbf67bf22,0x3f673f80,0x3e793f22,0xbf18be48,0xbf80bf62,
0xbf2cbf6d,0x3e16be95,0x3f5c3f0e,0x3f713f7f,0x3eac3f35,0xbf04bdc9,0xbf7dbf55,0xbf3ebf75,0x3d49bec4,0x3f4e3ef1,0x3f783f7b,0x3edb3f46,
0xbf7dbf6d,0xbeacbf46,0x3f2c3e48,0x3f783f75,0x3f040000,0x3f803f62,0x3edb3f55,0xbf18bdc9,0x3f4e3ec4,0x3f673f7f,0x3d493f0e,0xbf5cbef1,
0x3e793f35,0xbf3ebe95,0xbf71bf7b,0xbe16bf22,0x3e16bec4,0x3f713f22,0x3f3e3f7b,0xbe793e95,0x3f5c3f80,0xbd493ef1,0xbf67bf0e,0xbf4ebf7f,
0x3f183f6d,0xbedb3dc9,0xbf80bf55,0xbf04bf62,0xbf78bf35,0xbf2cbf75,0x3eacbe48,0x3f7d3f46,0x3f7d3f35,0x3edb3f62,0xbf3ebe48,0xbf5cbf7f,
0x3e79bec4,0x3f803f46,0x3eac3f55,0xbf4ebe95,0xbf180000,0xbf71bf75,0x3d49bf0e,0x3f783f22,0x3f043f6d,0xbf2cbdc9,0xbf67bf7b,0x3e16bef1,
0xbe16bf35,0x3f673ef1,0x3f2c3f7b,0xbf043dc9,0xbf78bf6d,0xbd49bf22,0x3f713f0e,0x3f183f75,0x3f4e3f80,0xbeac3e95,0xbf80bf55,0xbe79bf46,
0x3f5c3ec4,0x3f3e3f7f,0xbedb3e48,0xbf7dbf62,0xbedbbf6d,0x3f5c3e95,0x3f183f7b,0xbf3ebdc9,0xbd49bf35,0x3f7d3f22,0x3e793f55,0xbf71bef1,
0x3eacbec4,0x3f783f62,0xbe163f0e,0xbf80bf46,0x3f2c0000,0x3f4e3f7f,0xbf043e48,0xbf67bf75,0x3f673ec4,0x3f043f75,0xbf4ebe48,0xbf2cbf7f,
0x3f803f35,0x3e163f46,0xbf78bf0e,0xbeacbf62,0x3f713f6d,0xbe793ef1,0xbf7dbf55,0x3d49bf22,0x3f3e3f80,0xbf183dc9,0xbf5cbf7b,0x3edbbe95,
0x3f2c3f80,0xbf4ebdc9,0xbf04bf7b,0x3f673e95,0x3eac3f6d,0xbf78bef1,0xbe16bf55,0x3f803f22,0xbd493f35,0xbf7dbf46,0x3e79bf0e,0x3f713f62,
0xbedb3ec4,0xbf5cbf75,0x3f18be48,0x3f3e3f7f,0xbf3e0000,0xbf18bf7f,0x3f5c3e48,0x3edb3f75,0xbf71bec4,0xbe79bf62,0x3f7d3f0e,0x3d493f46,
0xbf80bf35,0x3e16bf22,0x3f783f55,0xbeac3ef1,0xbf67bf6d,0x3f04be95,0x3f4e3f7b,0xbf2c3dc9,0xbf043ec4,0xbf2cbf7f,0x3f673e48,0x3e163f62,
0x3f183f80,0xbf71be95,0xbd49bf55,0x3f783f46,0xbe79bf6d,0x3f803f22,0xbeac3f0e,0xbf4ebf75,0xbf7dbf35,0x3edbbef1,0x3f3e3f7b,0xbf5cbdc9,
0x3f5c3f6d,0xbf3e3dc9,0xbedbbf7b,0x3f7d3ef1,0x3f4e0000,0x3eac3f75,0xbf80bf0e,0x3e79bf22,0xbf78bec4,0x3d49bf46,0x3f713f55,0xbf183e95,
0xbe163f35,0xbf67bf62,0x3f2cbe48,0x3f043f7f,0x3e79bf35,0x3f3e3f75,0xbf71be48,0x3e16bf46,0x3f4e3f6d,0xbf67bdc9,0x3d49bf55,0x3f5c3f62,
0x3f043f80,0xbf80bef1,0x3edbbf0e,0x3f183f7f,0xbf7dbec4,0x3eacbf22,0x3f2c3f7b,0xbf78be95,0x3f783f35,0xbf2c3e95,0xbeacbf7b,0x3f7d3f22,
0xbf183ec4,0xbedbbf7f,0x3f803f0e,0xbf043ef1,0xbf5c0000,0xbd49bf62,0x3f673f55,0xbf4e3dc9,0xbe16bf6d,0x3f713f46,0xbf3e3e48,0xbe79bf75,
0xbf80bec4,0x3f18bef1,0x3e793f7b,0xbf67bf46,0x3f713f35,0xbf5c3dc9,0x3e16bf55,0x3f2c3f75,0xbf3ebf6d,0x3f7d3e95,0xbf043f0e,0xbeacbf7f,
0x3edb3f80,0xbf78bf22,0x3f4ebe48,0xbd493f62,0x3d493f6d,0xbf4ebf62,0x3f783e48,0xbedb3f22,0x3eacbf35,0x3f043f7f,0xbf7dbf0e,0x3f3ebe95,
0xbf2c3ec4,0xbe16bf75,0x3f5c3f55,0xbf71bdc9,0x3f670000,0xbe793f46,0xbf18bf7b,0x3f803ef1,0xbf710000,0x3f04bf22,0x3e163f7b,0xbf3ebf62,
0x3f803ec4,0xbf4e3e95,0x3e79bf55,0x3edb3f7f,0xbf67bf35,0x3f783dc9,0xbf183f0e,0xbd49bf75,0x3f2c3f6d,0xbf7dbef1,0x3f5cbe48,0xbeac3f46,
0x3eac3f80,0xbf5cbf46,0x3f7d3e48,0xbf2c3ef1,0x3d49bf6d,0x3f183f75,0xbf78bf0e,0x3f67bdc9,0xbedb3f35,0xbe79bf7f,0x3f4e3f55,0xbf80be95,
0x3f3ebec4,0xbe163f62,0xbf04bf7b,0x3f713f22,0xbf18bf6d,0x3f673f22,0xbf80be48,0x3f5cbe95,0x3f780000,0xbf3e3ef1,0x3eacbf55,0x3e163f7f,
0x3f7d3ec4,0xbf713dc9,0x3f2cbf0e,0xbe793f62,0xbf043f35,0x3d49bf75,0x3edb3f7b,0xbf4ebf46,0x3f4ebec4,0xbedb3f46,0xbd49bf7b,0x3f043f75,
0x3e793f80,0xbf2cbf62,0x3f713f0e,0xbf7dbdc9,0xbe163f6d,0xbeacbf7f,0x3f3e3f55,0xbf78bef1,0xbf5cbf35,0x3f803e95,0xbf673e48,0x3f18bf22,
0x3f4e3f35,0xbf71bef1,0x3f803e48,0xbf783dc9,0x3f5cbec4,0xbf2c3f22,0x3edbbf55,0xbe163f75,0xbf7d0000,0x3f67be95,0xbf3e3f0e,0x3f04bf46,
0xbe793f6d,0xbd49bf7f,0x3eac3f7b,0xbf18bf62,0x3f18bf35,0xbeac3f62,0x3d49bf7b,0x3e793f7f,0xbf04bf6d,0x3f3e3f46,0xbf67bf0e,0x3f7d3e95,
0x3e163f80,0xbedbbf75,0x3f2c3f55,0xbf5cbf22,0x3f783ec4,0xbf80bdc9,0x3f71be48,0xbf4e3ef1,0x3eacbf6d,0xbe793f75,0x3e16bf7b,0xbd493f7f,
0x3f2cbf35,0xbf183f46,0x3f04bf55,0xbedb3f62,0x3f67bec4,0xbf5c3ef1,0x3f4ebf0e,0xbf3e3f22,0x3f800000,0xbf7d3dc9,0x3f78be48,0xbf713e95,
0x3f713ec4,0xbf78be95,0x3f7d3e48,0xbf80bdc9,0x3f3e3f35,0xbf4ebf22,0x3f5c3f0e,0xbf67bef1,0x3edb3f6d,0xbf04bf62,0x3f183f55,0xbf2cbf46,
0x3d493f80,0xbe16bf7f,0x3e793f7b,0xbeacbf75,0xbd493f80,0x3e16bf7f,0xbe793f7b,0x3eacbf75,0xbedb3f6d,0x3f04bf62,0xbf183f55,0x3f2cbf46,
0xbf3e3f35,0x3f4ebf22,0xbf5c3f0e,0x3f67bef1,0xbf713ec4,0x3f78be95,0xbf7d3e48,0x3f80bdc9,0xbf800000,0x3f7d3dc9,0xbf78be48,0x3f713e95,
0xbf67bec4,0x3f5c3ef1,0xbf4ebf0e,0x3f3e3f22,0xbf2cbf35,0x3f183f46,0xbf04bf55,0x3edb3f62,0xbeacbf6d,0x3e793f75,0xbe16bf7b,0x3d493f7f,
0xbf783ec4,0x3f80bdc9,0xbf71be48,0x3f4e3ef1,0xbe163f80,0x3edbbf75,0xbf2c3f55,0x3f5cbf22,0x3f04bf6d,0xbf3e3f46,0x3f67bf0e,0xbf7d3e95,
0xbf18bf35,0x3eac3f62,0xbd49bf7b,0xbe793f7f,0x3e793f6d,0x3d49bf7f,0xbeac3f7b,0x3f18bf62,0x3f7d0000,0xbf67be95,0x3f3e3f0e,0xbf04bf46,
0xbf5cbec4,0x3f2c3f22,0xbedbbf55,0x3e163f75,0xbf4e3f35,0x3f71bef1,0xbf803e48,0x3f783dc9,0x3f5cbf35,0xbf803e95,0x3f673e48,0xbf18bf22,
0x3e163f6d,0x3eacbf7f,0xbf3e3f55,0x3f78bef1,0xbe793f80,0x3f2cbf62,0xbf713f0e,0x3f7dbdc9,0xbf4ebec4,0x3edb3f46,0x3d49bf7b,0xbf043f75,
0x3f043f35,0xbd49bf75,0xbedb3f7b,0x3f4ebf46,0xbf7d3ec4,0x3f713dc9,0xbf2cbf0e,0x3e793f62,0xbf780000,0x3f3e3ef1,0xbeacbf55,0xbe163f7f,
0x3f18bf6d,0xbf673f22,0x3f80be48,0xbf5cbe95,0xbf3ebec4,0x3e163f62,0x3f04bf7b,0xbf713f22,0x3edb3f35,0x3e79bf7f,0xbf4e3f55,0x3f80be95,
0xbd49bf6d,0xbf183f75,0x3f78bf0e,0xbf67bdc9,0xbeac3f80,0x3f5cbf46,0xbf7d3e48,0x3f2c3ef1,0xbf2c3f6d,0x3f7dbef1,0xbf5cbe48,0x3eac3f46,
0x3f67bf35,0xbf783dc9,0x3f183f0e,0x3d49bf75,0xbf803ec4,0x3f4e3e95,0xbe79bf55,0xbedb3f7f,0x3f710000,0xbf04bf22,0xbe163f7b,0x3f3ebf62,
0xbf670000,0x3e793f46,0x3f18bf7b,0xbf803ef1,0x3f2c3ec4,0x3e16bf75,0xbf5c3f55,0x3f71bdc9,0xbeacbf35,0xbf043f7f,0x3f7dbf0e,0xbf3ebe95,
0xbd493f6d,0x3f4ebf62,0xbf783e48,0x3edb3f22,0xbedb3f80,0x3f78bf22,0xbf4ebe48,0x3d493f62,0x3f3ebf6d,0xbf7d3e95,0x3f043f0e,0x3eacbf7f,
0xbf713f35,0x3f5c3dc9,0xbe16bf55,0xbf2c3f75,0x3f80bec4,0xbf18bef1,0xbe793f7b,0x3f67bf46,0x3e16bf6d,0xbf713f46,0x3f3e3e48,0x3e79bf75,
0x3f5c0000,0x3d49bf62,0xbf673f55,0x3f4e3dc9,0x3f183ec4,0x3edbbf7f,0xbf803f0e,0x3f043ef1,0xbf783f35,0x3f2c3e95,0x3eacbf7b,0xbf7d3f22,
0x3f7dbec4,0xbeacbf22,0xbf2c3f7b,0x3f78be95,0xbf043f80,0x3f80bef1,0xbedbbf0e,0xbf183f7f,0xbf4e3f6d,0x3f67bdc9,0xbd49bf55,0xbf5c3f62,
0xbe79bf35,0xbf3e3f75,0x3f71be48,0xbe16bf46,0x3e163f35,0x3f67bf62,0xbf2cbe48,0xbf043f7f,0x3f78bec4,0xbd49bf46,0xbf713f55,0x3f183e95,
0xbf4e0000,0xbeac3f75,0x3f80bf0e,0xbe79bf22,0xbf5c3f6d,0x3f3e3dc9,0x3edbbf7b,0xbf7d3ef1,0x3f7dbf35,0xbedbbef1,0xbf3e3f7b,0x3f5cbdc9,
0x3e79bf6d,0xbf803f22,0x3eac3f0e,0x3f4ebf75,0xbf183f80,0x3f71be95,0x3d49bf55,0xbf783f46,0x3f043ec4,0x3f2cbf7f,0xbf673e48,0xbe163f62,
0x3f67bf6d,0xbf04be95,0xbf4e3f7b,0x3f2c3dc9,0x3f80bf35,0xbe16bf22,0xbf783f55,0x3eac3ef1,0x3f71bec4,0x3e79bf62,0xbf7d3f0e,0xbd493f46,
0x3f3e0000,0x3f18bf7f,0xbf5c3e48,0xbedb3f75,0x3edb3ec4,0x3f5cbf75,0xbf18be48,0xbf3e3f7f,0x3d493f35,0x3f7dbf46,0xbe79bf0e,0xbf713f62,
0xbeac3f6d,0x3f78bef1,0x3e16bf55,0xbf803f22,0xbf2c3f80,0x3f4ebdc9,0x3f04bf7b,0xbf673e95,0xbf3e3f80,0x3f183dc9,0x3f5cbf7b,0xbedbbe95,
0xbf713f6d,0x3e793ef1,0x3f7dbf55,0xbd49bf22,0xbf803f35,0xbe163f46,0x3f78bf0e,0x3eacbf62,0xbf673ec4,0xbf043f75,0x3f4ebe48,0x3f2cbf7f,
0xbf2c0000,0xbf4e3f7f,0x3f043e48,0x3f67bf75,0xbeacbec4,0xbf783f62,0x3e163f0e,0x3f80bf46,0x3d49bf35,0xbf7d3f22,0xbe793f55,0x3f71bef1,
0x3edbbf6d,0xbf5c3e95,0xbf183f7b,0x3f3ebdc9,0xbf5c3ec4,0xbf3e3f7f,0x3edb3e48,0x3f7dbf62,0xbf4e3f80,0x3eac3e95,0x3f80bf55,0x3e79bf46,
0x3f78bf6d,0x3d49bf22,0xbf713f0e,0xbf183f75,0x3e16bf35,0xbf673ef1,0xbf2c3f7b,0x3f043dc9,0xbf043f6d,0x3f2cbdc9,0x3f67bf7b,0xbe16bef1,
0x3f180000,0x3f71bf75,0xbd49bf0e,0xbf783f22,0xbe79bec4,0xbf803f46,0xbeac3f55,0x3f4ebe95,0xbf7d3f35,0xbedb3f62,0x3f3ebe48,0x3f5cbf7f,
0x3f78bf35,0x3f2cbf75,0xbeacbe48,0xbf7d3f46,0xbf183f6d,0x3edb3dc9,0x3f80bf55,0x3f04bf62,0xbf5c3f80,0x3d493ef1,0x3f67bf0e,0x3f4ebf7f,
0xbe16bec4,0xbf713f22,0xbf3e3f7b,0x3e793e95,0xbe793f35,0x3f3ebe95,0x3f71bf7b,0x3e16bf22,0xbf4e3ec4,0xbf673f7f,0xbd493f0e,0x3f5cbef1,
0xbf040000,0xbf803f62,0xbedb3f55,0x3f18bdc9,0x3f7dbf6d,0x3eacbf46,0xbf2c3e48,0xbf783f75,0xbd49bec4,0xbf4e3ef1,0xbf783f7b,0xbedb3f46,
0xbeac3f35,0x3f04bdc9,0x3f7dbf55,0x3f3ebf75,0x3f2cbf6d,0xbe16be95,0xbf5c3f0e,0xbf713f7f,0xbf673f80,0xbe793f22,0x3f18be48,0x3f80bf62,
0xbf803f6d,0xbf183f62,0x3e793e48,0x3f67bf22,0x3f71bf35,0x3f5cbf7f,0x3e16bf0e,0xbf2c3e95,0xbf3e3ec4,0xbf7d3f75,0xbf043f55,0x3eac3dc9,
0x3edb0000,0x3f78bf46,0x3f4ebf7b,0x3d49bef1,0xbeac0000,0xbf5c3f22,0xbf7d3f7b,0xbf2c3f62,0xbd493ec4,0x3f18be95,0x3f78bf55,0x3f67bf7f,
0x3edbbf35,0xbe79bdc9,0xbf4e3f0e,0xbf803f75,0xbf3e3f6d,0xbe163ef1,0x3f04be48,0x3f71bf46,0xbf713f80,0xbf043f46,0x3e163e48,0x3f3ebef1,
0x3f80bf6d,0x3f4ebf75,0x3e79bf0e,0xbedb3dc9,0xbf673f35,0xbf783f7f,0xbf183f55,0x3d493e95,0x3f2cbec4,0x3f7dbf62,0x3f5cbf7b,0x3eacbf22,
0x3f4ebf6d,0x3edbbf22,0xbd49be48,0xbf043e95,0x3e790000,0x3f2cbef1,0x3f71bf55,0x3f7dbf7f,0xbe163ec4,0x3eacbdc9,0x3f3ebf0e,0x3f78bf62,
0xbf5c3f35,0xbf803f75,0xbf673f7b,0xbf183f46,0x3f18bec4,0x3f67bf46,0x3f80bf7b,0x3f5cbf75,0xbf783f80,0xbf3e3f62,0xbeac3f0e,0x3e163dc9,
0xbf7d3f6d,0xbf713f7f,0xbf2c3f55,0xbe793ef1,0x3f04bf35,0x3d49be95,0xbedb3e48,0xbf4e3f22,0xbf183f35,0xbeac3ef1,0xbd493e48,0x3e79bdc9,
0x3f04bec4,0x3f3ebf22,0x3f67bf55,0x3f7dbf75,0xbe160000,0xbedb3e95,0xbf2c3f0e,0xbf5c3f46,0xbf783f6d,0xbf803f7f,0xbf713f7b,0xbf4e3f62,
0x3f4ebf35,0x3f71bf62,0x3f80bf7b,0x3f78bf7f,0x3f5cbf6d,0x3f2cbf46,0x3edbbf0e,0x3e16be95,0xbf7d3f80,0xbf673f75,0xbf3e3f55,0xbf043f22,
0xbe793ec4,0x3d493dc9,0x3eacbe48,0x3f18bef1,0x3f71bf6d,0x3f78bf75,0x3f7dbf7b,0x3f80bf7f,0x3f3ebf35,0x3f4ebf46,0x3f5cbf55,0x3f67bf62,
0x3edbbec4,0x3f04bef1,0x3f18bf0e,0x3f2cbf22,0x3d490000,0x3e16bdc9,0x3e79be48,0x3eacbe95,0xbeac3ec4,0xbe793e95,0xbe163e48,0xbd493dc9,
0xbf2c3f35,0xbf183f22,0xbf043f0e,0xbedb3ef1,0xbf673f6d,0xbf5c3f62,0xbf4e3f55,0xbf3e3f46,0xbf803f80,0xbf7d3f7f,0xbf783f7b,0xbf713f75,
0xbd490000,0xbe16bdc9,0xbe79be48,0xbeacbe95,0xbedbbec4,0xbf04bef1,0xbf18bf0e,0xbf2cbf22,0xbf3ebf35,0xbf4ebf46,0xbf5cbf55,0xbf67bf62,
0xbf71bf6d,0xbf78bf75,0xbf7dbf7b,0xbf80bf7f,0xbf80bf80,0xbf7dbf7f,0xbf78bf7b,0xbf71bf75,0xbf67bf6d,0xbf5cbf62,0xbf4ebf55,0xbf3ebf46,
0xbf2cbf35,0xbf18bf22,0xbf04bf0e,0xbedbbef1,0xbeacbec4,0xbe79be95,0xbe16be48,0xbd49bdc9,0xbf78bf6d,0xbf80bf7f,0xbf71bf7b,0xbf4ebf62,
0xbe160000,0xbedbbe95,0xbf2cbf0e,0xbf5cbf46,0x3f043ec4,0x3f3e3f22,0x3f673f55,0x3f7d3f75,0xbf18bf35,0xbeacbef1,0xbd49be48,0x3e793dc9,
0x3e793ec4,0xbd493dc9,0xbeacbe48,0xbf18bef1,0x3f7d3f80,0x3f673f75,0x3f3e3f55,0x3f043f22,0xbf5cbf6d,0xbf2cbf46,0xbedbbf0e,0xbe16be95,
0xbf4ebf35,0xbf71bf62,0xbf80bf7b,0xbf78bf7f,0x3f5c3f35,0x3f803f75,0x3f673f7b,0x3f183f46,0x3e163ec4,0xbeacbdc9,0xbf3ebf0e,0xbf78bf62,
0xbe790000,0xbf2cbef1,0xbf71bf55,0xbf7dbf7f,0xbf4ebf6d,0xbedbbf22,0x3d49be48,0x3f043e95,0x3f043f35,0x3d493e95,0xbedbbe48,0xbf4ebf22,
0xbf7dbf6d,0xbf71bf7f,0xbf2cbf55,0xbe79bef1,0xbf78bf80,0xbf3ebf62,0xbeacbf0e,0x3e16bdc9,0x3f183ec4,0x3f673f46,0x3f803f7b,0x3f5c3f75,
0xbf3ebf6d,0xbe16bef1,0x3f043e48,0x3f713f46,0x3edb3f35,0xbe793dc9,0xbf4ebf0e,0xbf80bf75,0xbd49bec4,0x3f183e95,0x3f783f55,0x3f673f7f,
0xbeac0000,0xbf5cbf22,0xbf7dbf7b,0xbf2cbf62,0xbf2cbec4,0xbf7dbf62,0xbf5cbf7b,0xbeacbf22,0x3f673f35,0x3f783f7f,0x3f183f55,0xbd493e95,
0xbf80bf6d,0xbf4ebf75,0xbe79bf0e,0x3edb3dc9,0x3f713f80,0x3f043f46,0xbe163e48,0xbf3ebef1,0xbf67bf80,0xbe79bf22,0x3f183e48,0x3f803f62,
0x3f2c3f6d,0xbe163e95,0xbf5cbf0e,0xbf71bf7f,0xbeacbf35,0x3f043dc9,0x3f7d3f55,0x3f3e3f75,0xbd493ec4,0xbf4ebef1,0xbf78bf7b,0xbedbbf46,
0xbedb0000,0xbf78bf46,0xbf4ebf7b,0xbd49bef1,0x3f3e3ec4,0x3f7d3f75,0x3f043f55,0xbeac3dc9,0xbf71bf35,0xbf5cbf7f,0xbe16bf0e,0x3f2c3e95,
0x3f803f6d,0x3f183f62,0xbe793e48,0xbf67bf22,0x3e16bec4,0x3f713f22,0x3f3e3f7b,0xbe793e95,0x3f5c3f80,0xbd493ef1,0xbf67bf0e,0xbf4ebf7f,
0x3f183f6d,0xbedb3dc9,0xbf80bf55,0xbf04bf62,0xbf78bf35,0xbf2cbf75,0x3eacbe48,0x3f7d3f46,0x3f7d3f6d,0x3eac3f46,0xbf2cbe48,0xbf78bf75,
0xbf040000,0xbf80bf62,0xbedbbf55,0x3f183dc9,0xbf4ebec4,0xbf67bf7f,0xbd49bf0e,0x3f5c3ef1,0xbe79bf35,0x3f3e3e95,0x3f713f7b,0x3e163f22,
0x3e163f35,0xbf67bef1,0xbf2cbf7b,0x3f04bdc9,0x3f783f6d,0x3d493f22,0xbf71bf0e,0xbf18bf75,0xbf4ebf80,0x3eacbe95,0x3f803f55,0x3e793f46,
0xbf5cbec4,0xbf3ebf7f,0x3edbbe48,0x3f7d3f62,0x3f7d3f35,0x3edb3f62,0xbf3ebe48,0xbf5cbf7f,0x3e79bec4,0x3f803f46,0x3eac3f55,0xbf4ebe95,
0xbf180000,0xbf71bf75,0x3d49bf0e,0x3f783f22,0x3f043f6d,0xbf2cbdc9,0xbf67bf7b,0x3e16bef1,0x3f673ec4,0x3f043f75,0xbf4ebe48,0xbf2cbf7f,
0x3f803f35,0x3e163f46,0xbf78bf0e,0xbeacbf62,0x3f713f6d,0xbe793ef1,0xbf7dbf55,0x3d49bf22,0x3f3e3f80,0xbf183dc9,0xbf5cbf7b,0x3edbbe95,
0x3edb3f6d,0xbf5cbe95,0xbf18bf7b,0x3f3e3dc9,0x3d493f35,0xbf7dbf22,0xbe79bf55,0x3f713ef1,0xbeac3ec4,0xbf78bf62,0x3e16bf0e,0x3f803f46,
0xbf2c0000,0xbf4ebf7f,0x3f04be48,0x3f673f75,0xbf3e0000,0xbf18bf7f,0x3f5c3e48,0x3edb3f75,0xbf71bec4,0xbe79bf62,0x3f7d3f0e,0x3d493f46,
0xbf80bf35,0x3e16bf22,0x3f783f55,0xbeac3ef1,0xbf67bf6d,0x3f04be95,0x3f4e3f7b,0xbf2c3dc9,0xbf2cbf80,0x3f4e3dc9,0x3f043f7b,0xbf67be95,
0xbeacbf6d,0x3f783ef1,0x3e163f55,0xbf80bf22,0x3d49bf35,0x3f7d3f46,0xbe793f0e,0xbf71bf62,0x3edbbec4,0x3f5c3f75,0xbf183e48,0xbf3ebf7f,
0xbf5cbf6d,0x3f3ebdc9,0x3edb3f7b,0xbf7dbef1,0xbf4e0000,0xbeacbf75,0x3f803f0e,0xbe793f22,0x3f783ec4,0xbd493f46,0xbf71bf55,0x3f18be95,
0x3e16bf35,0x3f673f62,0xbf2c3e48,0xbf04bf7f,0xbf043ec4,0xbf2cbf7f,0x3f673e48,0x3e163f62,0x3f183f80,0xbf71be95,0xbd49bf55,0x3f783f46,
0xbe79bf6d,0x3f803f22,0xbeac3f0e,0xbf4ebf75,0xbf7dbf35,0x3edbbef1,0x3f3e3f7b,0xbf5cbdc9,0x3f783f35,0xbf2c3e95,0xbeacbf7b,0x3f7d3f22,
0xbf183ec4,0xbedbbf7f,0x3f803f0e,0xbf043ef1,0xbf5c0000,0xbd49bf62,0x3f673f55,0xbf4e3dc9,0xbe16bf6d,0x3f713f46,0xbf3e3e48,0xbe79bf75,
0xbe793f35,0xbf3ebf75,0x3f713e48,0xbe163f46,0xbf4ebf6d,0x3f673dc9,0xbd493f55,0xbf5cbf62,0xbf04bf80,0x3f803ef1,0xbedb3f0e,0xbf18bf7f,
0x3f7d3ec4,0xbeac3f22,0xbf2cbf7b,0x3f783e95,0xbd49bf6d,0x3f4e3f62,0xbf78be48,0x3edbbf22,0xbeac3f35,0xbf04bf7f,0x3f7d3f0e,0xbf3e3e95,
0x3f2cbec4,0x3e163f75,0xbf5cbf55,0x3f713dc9,0xbf670000,0x3e79bf46,0x3f183f7b,0xbf80bef1,0xbf80bec4,0x3f18bef1,0x3e793f7b,0xbf67bf46,
0x3f713f35,0xbf5c3dc9,0x3e16bf55,0x3f2c3f75,0xbf3ebf6d,0x3f7d3e95,0xbf043f0e,0xbeacbf7f,0x3edb3f80,0xbf78bf22,0x3f4ebe48,0xbd493f62,
0xbeacbf80,0x3f5c3f46,0xbf7dbe48,0x3f2cbef1,0xbd493f6d,0xbf18bf75,0x3f783f0e,0xbf673dc9,0x3edbbf35,0x3e793f7f,0xbf4ebf55,0x3f803e95,
0xbf3e3ec4,0x3e16bf62,0x3f043f7b,0xbf71bf22,0xbf710000,0x3f04bf22,0x3e163f7b,0xbf3ebf62,0x3f803ec4,0xbf4e3e95,0x3e79bf55,0x3edb3f7f,
0xbf67bf35,0x3f783dc9,0xbf183f0e,0xbd49bf75,0x3f2c3f6d,0xbf7dbef1,0x3f5cbe48,0xbeac3f46,0x3f4ebec4,0xbedb3f46,0xbd49bf7b,0x3f043f75,
0x3e793f80,0xbf2cbf62,0x3f713f0e,0xbf7dbdc9,0xbe163f6d,0xbeacbf7f,0x3f3e3f55,0xbf78bef1,0xbf5cbf35,0x3f803e95,0xbf673e48,0x3f18bf22,
0x3f183f6d,0xbf67bf22,0x3f803e48,0xbf5c3e95,0xbf780000,0x3f3ebef1,0xbeac3f55,0xbe16bf7f,0xbf7dbec4,0x3f71bdc9,0xbf2c3f0e,0x3e79bf62,
0x3f04bf35,0xbd493f75,0xbedbbf7b,0x3f4e3f46,0xbf183f35,0x3eacbf62,0xbd493f7b,0xbe79bf7f,0x3f043f6d,0xbf3ebf46,0x3f673f0e,0xbf7dbe95,
0xbe16bf80,0x3edb3f75,0xbf2cbf55,0x3f5c3f22,0xbf78bec4,0x3f803dc9,0xbf713e48,0x3f4ebef1,0x3f4e3f35,0xbf71bef1,0x3f803e48,0xbf783dc9,
0x3f5cbec4,0xbf2c3f22,0x3edbbf55,0xbe163f75,0xbf7d0000,0x3f67be95,0xbf3e3f0e,0x3f04bf46,0xbe793f6d,0xbd49bf7f,0x3eac3f7b,0xbf18bf62,
0x3f713ec4,0xbf78be95,0x3f7d3e48,0xbf80bdc9,0x3f3e3f35,0xbf4ebf22,0x3f5c3f0e,0xbf67bef1,0x3edb3f6d,0xbf04bf62,0x3f183f55,0xbf2cbf46,
0x3d493f80,0xbe16bf7f,0x3e793f7b,0xbeacbf75,0xbeac3f6d,0x3e79bf75,0xbe163f7b,0x3d49bf7f,0xbf2c3f35,0x3f18bf46,0xbf043f55,0x3edbbf62,
0xbf673ec4,0x3f5cbef1,0xbf4e3f0e,0x3f3ebf22,0xbf800000,0x3f7dbdc9,0xbf783e48,0x3f71be95,0xbf800000,0x3f7d3dc9,0xbf78be48,0x3f713e95,
0xbf67bec4,0x3f5c3ef1,0xbf4ebf0e,0x3f3e3f22,0xbf2cbf35,0x3f183f46,0xbf04bf55,0x3edb3f62,0xbeacbf6d,0x3e793f75,0xbe16bf7b,0x3d493f7f,
0x3d49bf80,0xbe163f7f,0x3e79bf7b,0xbeac3f75,0x3edbbf6d,0xbf043f62,0x3f18bf55,0xbf2c3f46,0x3f3ebf35,0xbf4e3f22,0x3f5cbf0e,0xbf673ef1,
0x3f71bec4,0xbf783e95,0x3f7dbe48,0xbf803dc9,0xbe79bf6d,0xbd493f7f,0x3eacbf7b,0xbf183f62,0xbf7d0000,0x3f673e95,0xbf3ebf0e,0x3f043f46,
0x3f5c3ec4,0xbf2cbf22,0x3edb3f55,0xbe16bf75,0x3f4ebf35,0xbf713ef1,0x3f80be48,0xbf78bdc9,0xbf783ec4,0x3f80bdc9,0xbf71be48,0x3f4e3ef1,
0xbe163f80,0x3edbbf75,0xbf2c3f55,0x3f5cbf22,0x3f04bf6d,0xbf3e3f46,0x3f67bf0e,0xbf7d3e95,0xbf18bf35,0x3eac3f62,0xbd49bf7b,0xbe793f7f,
0x3f043f35,0xbd49bf75,0xbedb3f7b,0x3f4ebf46,0xbf7d3ec4,0x3f713dc9,0xbf2cbf0e,0x3e793f62,0xbf780000,0x3f3e3ef1,0xbeacbf55,0xbe163f7f,
0x3f18bf6d,0xbf673f22,0x3f80be48,0xbf5cbe95,0xbf5c3f35,0x3f80be95,0xbf67be48,0x3f183f22,0xbe16bf6d,0xbeac3f7f,0x3f3ebf55,0xbf783ef1,
0x3e79bf80,0xbf2c3f62,0x3f71bf0e,0xbf7d3dc9,0x3f4e3ec4,0xbedbbf46,0xbd493f7b,0x3f04bf75,0x3f2cbf6d,0xbf7d3ef1,0x3f5c3e48,0xbeacbf46,
0xbf673f35,0x3f78bdc9,0xbf18bf0e,0xbd493f75,0x3f80bec4,0xbf4ebe95,0x3e793f55,0x3edbbf7f,0xbf710000,0x3f043f22,0x3e16bf7b,0xbf3e3f62,
0xbf3ebec4,0x3e163f62,0x3f04bf7b,0xbf713f22,0x3edb3f35,0x3e79bf7f,0xbf4e3f55,0x3f80be95,0xbd49bf6d,0xbf183f75,0x3f78bf0e,0xbf67bdc9,
0xbeac3f80,0x3f5cbf46,0xbf7d3e48,0x3f2c3ef1,0x3edbbf80,0xbf783f22,0x3f4e3e48,0xbd49bf62,0xbf3e3f6d,0x3f7dbe95,0xbf04bf0e,0xbeac3f7f,
0x3f71bf35,0xbf5cbdc9,0x3e163f55,0x3f2cbf75,0xbf803ec4,0x3f183ef1,0x3e79bf7b,0xbf673f46,0xbf670000,0x3e793f46,0x3f18bf7b,0xbf803ef1,
0x3f2c3ec4,0x3e16bf75,0xbf5c3f55,0x3f71bdc9,0xbeacbf35,0xbf043f7f,0x3f7dbf0e,0xbf3ebe95,0xbd493f6d,0x3f4ebf62,0xbf783e48,0x3edb3f22,
0x3f7dbec4,0xbeacbf22,0xbf2c3f7b,0x3f78be95,0xbf043f80,0x3f80bef1,0xbedbbf0e,0xbf183f7f,0xbf4e3f6d,0x3f67bdc9,0xbd49bf55,0xbf5c3f62,
0xbe79bf35,0xbf3e3f75,0x3f71be48,0xbe16bf46,0xbe163f6d,0x3f71bf46,0xbf3ebe48,0xbe793f75,0xbf5c0000,0xbd493f62,0x3f67bf55,0xbf4ebdc9,
0xbf18bec4,0xbedb3f7f,0x3f80bf0e,0xbf04bef1,0x3f78bf35,0xbf2cbe95,0xbeac3f7b,0x3f7dbf22,0xbf7d3f35,0x3edb3ef1,0x3f3ebf7b,0xbf5c3dc9,
0xbe793f6d,0x3f80bf22,0xbeacbf0e,0xbf4e3f75,0x3f18bf80,0xbf713e95,0xbd493f55,0x3f78bf46,0xbf04bec4,0xbf2c3f7f,0x3f67be48,0x3e16bf62,
0x3e163f35,0x3f67bf62,0xbf2cbe48,0xbf043f7f,0x3f78bec4,0xbd49bf46,0xbf713f55,0x3f183e95,0xbf4e0000,0xbeac3f75,0x3f80bf0e,0xbe79bf22,
0xbf5c3f6d,0x3f3e3dc9,0x3edbbf7b,0xbf7d3ef1,0x3edb3ec4,0x3f5cbf75,0xbf18be48,0xbf3e3f7f,0x3d493f35,0x3f7dbf46,0xbe79bf0e,0xbf713f62,
0xbeac3f6d,0x3f78bef1,0x3e16bf55,0xbf803f22,0xbf2c3f80,0x3f4ebdc9,0x3f04bf7b,0xbf673e95,0xbf673f6d,0x3f043e95,0x3f4ebf7b,0xbf2cbdc9,
0xbf803f35,0x3e163f22,0x3f78bf55,0xbeacbef1,0xbf713ec4,0xbe793f62,0x3f7dbf0e,0x3d49bf46,0xbf3e0000,0xbf183f7f,0x3f5cbe48,0x3edbbf75,
0xbf2c0000,0xbf4e3f7f,0x3f043e48,0x3f67bf75,0xbeacbec4,0xbf783f62,0x3e163f0e,0x3f80bf46,0x3d49bf35,0xbf7d3f22,0xbe793f55,0x3f71bef1,
0x3edbbf6d,0xbf5c3e95,0xbf183f7b,0x3f3ebdc9,0x3f3ebf80,0xbf18bdc9,0xbf5c3f7b,0x3edb3e95,0x3f71bf6d,0xbe79bef1,0xbf7d3f55,0x3d493f22,
0x3f80bf35,0x3e16bf46,0xbf783f0e,0xbeac3f62,0x3f67bec4,0x3f04bf75,0xbf4e3e48,0xbf2c3f7f,0x3f04bf6d,0xbf2c3dc9,0xbf673f7b,0x3e163ef1,
0xbf180000,0xbf713f75,0x3d493f0e,0x3f78bf22,0x3e793ec4,0x3f80bf46,0x3eacbf55,0xbf4e3e95,0x3f7dbf35,0x3edbbf62,0xbf3e3e48,0xbf5c3f7f,
0xbf5c3ec4,0xbf3e3f7f,0x3edb3e48,0x3f7dbf62,0xbf4e3f80,0x3eac3e95,0x3f80bf55,0x3e79bf46,0x3f78bf6d,0x3d49bf22,0xbf713f0e,0xbf183f75,
0x3e16bf35,0xbf673ef1,0xbf2c3f7b,0x3f043dc9,0xbe793f35,0x3f3ebe95,0x3f71bf7b,0x3e16bf22,0xbf4e3ec4,0xbf673f7f,0xbd493f0e,0x3f5cbef1,
0xbf040000,0xbf803f62,0xbedb3f55,0x3f18bdc9,0x3f7dbf6d,0x3eacbf46,0xbf2c3e48,0xbf783f75,0xbf783f35,0xbf2c3f75,0x3eac3e48,0x3f7dbf46,
0x3f18bf6d,0xbedbbdc9,0xbf803f55,0xbf043f62,0x3f5cbf80,0xbd49bef1,0xbf673f0e,0xbf4e3f7f,0x3e163ec4,0x3f71bf22,0x3f3ebf7b,0xbe79be95,
0x3f80bf6d,0x3f18bf62,0xbe79be48,0xbf673f22,0xbf713f35,0xbf5c3f7f,0xbe163f0e,0x3f2cbe95,0x3f3ebec4,0x3f7dbf75,0x3f04bf55,0xbeacbdc9,
0xbedb0000,0xbf783f46,0xbf4e3f7b,0xbd493ef1,0xbd49bec4,0xbf4e3ef1,0xbf783f7b,0xbedb3f46,0xbeac3f35,0x3f04bdc9,0x3f7dbf55,0x3f3ebf75,
0x3f2cbf6d,0xbe16be95,0xbf5c3f0e,0xbf713f7f,0xbf673f80,0xbe793f22,0x3f18be48,0x3f80bf62,0x3f71bf80,0x3f04bf46,0xbe16be48,0xbf3e3ef1,
0xbf803f6d,0xbf4e3f75,0xbe793f0e,0x3edbbdc9,0x3f67bf35,0x3f78bf7f,0x3f18bf55,0xbd49be95,0xbf2c3ec4,0xbf7d3f62,0xbf5c3f7b,0xbeac3f22,
0xbeac0000,0xbf5c3f22,0xbf7d3f7b,0xbf2c3f62,0xbd493ec4,0x3f18be95,0x3f78bf55,0x3f67bf7f,0x3edbbf35,0xbe79bdc9,0xbf4e3f0e,0xbf803f75,
0xbf3e3f6d,0xbe163ef1,0x3f04be48,0x3f71bf46,0x3f18bec4,0x3f67bf46,0x3f80bf7b,0x3f5cbf75,0xbf783f80,0xbf3e3f62,0xbeac3f0e,0x3e163dc9,
0xbf7d3f6d,0xbf713f7f,0xbf2c3f55,0xbe793ef1,0x3f04bf35,0x3d49be95,0xbedb3e48,0xbf4e3f22,0xbf4e3f6d,0xbedb3f22,0x3d493e48,0x3f04be95,
0xbe790000,0xbf2c3ef1,0xbf713f55,0xbf7d3f7f,0x3e16bec4,0xbeac3dc9,0xbf3e3f0e,0xbf783f62,0x3f5cbf35,0x3f80bf75,0x3f67bf7b,0x3f18bf46,
0xbf4e3f35,0xbf713f62,0xbf803f7b,0xbf783f7f,0xbf5c3f6d,0xbf2c3f46,0xbedb3f0e,0xbe163e95,0x3f7dbf80,0x3f67bf75,0x3f3ebf55,0x3f04bf22,
0x3e79bec4,0xbd49bdc9,0xbeac3e48,0xbf183ef1,0xbf183f35,0xbeac3ef1,0xbd493e48,0x3e79bdc9,0x3f04bec4,0x3f3ebf22,0x3f67bf55,0x3f7dbf75,
0xbe160000,0xbedb3e95,0xbf2c3f0e,0xbf5c3f46,0xbf783f6d,0xbf803f7f,0xbf713f7b,0xbf4e3f62,0xbeac3ec4,0xbe793e95,0xbe163e48,0xbd493dc9,
0xbf2c3f35,0xbf183f22,0xbf043f0e,0xbedb3ef1,0xbf673f6d,0xbf5c3f62,0xbf4e3f55,0xbf3e3f46,0xbf803f80,0xbf7d3f7f,0xbf783f7b,0xbf713f75,
0xbf713f6d,0xbf783f75,0xbf7d3f7b,0xbf803f7f,0xbf3e3f35,0xbf4e3f46,0xbf5c3f55,0xbf673f62,0xbedb3ec4,0xbf043ef1,0xbf183f0e,0xbf2c3f22,
0xbd490000,0xbe163dc9,0xbe793e48,0xbeac3e95,
};
__device__ __align__(128) const uint32_t T_Gi[4096] = {
0x3b4d3acd,0x3b4d3b4d,0x3b4d3b4d,0x3b4d3b4d,0x3b4d3b4d,0x3b4d3b4d,0x3b4d3b4d,0x3b4d3b4d,0x3b4d3b4d,0x3b4d3b4d,0x3b4d3b4d,0x3b4d3b4d,
0x3b4d3b4d,0x3b4d3b4d,0x3b4d3b4d,0x3b4d3b4d,0x3acd,0x0,0x0,0x0,0x0,0x0,0x0,0x0,
0x0,0x0,0x0,0x0,0x0,0x0,0x0,0x0,0x3b023b11,0x3ac13ae4,0x3a6e3a9d,0x39a13a20,
0x3b4c3acd,0x3b443b49,0x3b353b3d,0x3b1e3b2a,0xbb1ebb11,0xbb35bb2a,0xbb44bb3d,0xbb4cbb49,0xb9a10000,0xba6eba20,0xbac1ba9d,0xbb02bae4,
0xbb1ebb11,0xbb35bb2a,0xbb44bb3d,0xbb4cbb49,0xb9a1bacd,0xba6eba20,0xbac1ba9d,0xbb02bae4,0xbb02bb11,0xbac1bae4,0xba6eba9d,0xb9a1ba20,
0xbb4cbb4d,0xbb44bb49,0xbb35bb3d,0xbb1ebb2a,0xbb49bb4d,0xbb2abb3d,0xbae4bb11,0xba20ba9d,0x3a200000,0x3ae43a9d,0x3b2a3b11,0x3b493b3d,
0x3b493acd,0x3b2a3b3d,0x3ae43b11,0x3a203a9d,0xba200000,0xbae4ba9d,0xbb2abb11,0xbb49bb3d,0x3a200000,0x3ae43a9d,0x3b2a3b11,0x3b493b3d,
0x3b493b4d,0x3b2a3b3d,0x3ae43b11,0x3a203a9d,0xba203acd,0xbae4ba9d,0xbb2abb11,0xbb49bb3d,0xbb49bb4d,0xbb2abb3d,0xbae4bb11,0xba20ba9d,
0x3ac13b11,0xb9a13a20,0xbb02ba9d,0xbb44bb2a,0x3a6e0000,0x3b1e3ae4,0x3b4c3b3d,0x3b353b49,0xbb35bb11,0xbb4cbb49,0xbb1ebb3d,0xba6ebae4,
0x3b443acd,0x3b023b2a,0x39a13a9d,0xbac1ba20,0xbb35bb11,0xbb4cbb49,0xbb1ebb3d,0xba6ebae4,0x3b443b4d,0x3b023b2a,0x39a13a9d,0xbac1ba20,
0xbac1bb11,0x39a1ba20,0x3b023a9d,0x3b443b2a,0xba6ebacd,0xbb1ebae4,0xbb4cbb3d,0xbb35bb49,0xba9d3acd,0xbb3dbb11,0xbb3dbb4d,0xba9dbb11,
0x3a9d0000,0x3b3d3b11,0x3b3d3b4d,0x3a9d3b11,0xba9d0000,0xbb3dbb11,0xbb3dbb4d,0xba9dbb11,0x3a9d0000,0x3b3d3b11,0x3b3d3b4d,0x3a9d3b11,
0x3b3d3acd,0x3a9d3b11,0xba9d0000,0xbb3dbb11,0xbb3dbb4d,0xba9dbb11,0x3a9d0000,0x3b3d3b11,0x3b3d3b4d,0x3a9d3b11,0xba9d0000,0xbb3dbb11,
0xbb3dbb4d,0xba9dbb11,0x3a9d0000,0x3b3d3b11,0x3b443b11,0x3b1e3b49,0xb9a13a9d,0xbb35bae4,0xbac1bacd,0xbb4cbb2a,0xbb02bb3d,0x3a6eba20,
0x3a6e3b11,0xbb02ba20,0xbb4cbb3d,0xbac1bb2a,0xbb35bb4d,0xb9a1bae4,0x3b1e3a9d,0x3b443b49,0xba6ebb11,0x3b023a20,0x3b4c3b3d,0x3ac13b2a,
0x3b353acd,0x39a13ae4,0xbb1eba9d,0xbb44bb49,0x3b443b11,0x3b1e3b49,0xb9a13a9d,0xbb35bae4,0xbac10000,0xbb4cbb2a,0xbb02bb3d,0x3a6eba20,
0x3ae40000,0x3b493b3d,0x3a203b11,0xbb2aba9d,0xbb2abb4d,0x3a20ba9d,0x3b493b11,0x3ae43b3d,0xbae43acd,0xbb49bb3d,0xba20bb11,0x3b2a3a9d,
0x3b2a3b4d,0xba203a9d,0xbb49bb11,0xbae4bb3d,0xbb2abb4d,0x3a20ba9d,0x3b493b11,0x3ae43b3d,0xbae40000,0xbb49bb3d,0xba20bb11,0x3b2a3a9d,
0x3b2a3acd,0xba203a9d,0xbb49bb11,0xbae4bb3d,0x3ae40000,0x3b493b3d,0x3a203b11,0xbb2aba9d,0x3b4c3b11,0x3a6e3b2a,0xbb35ba9d,0xbb02bb49,
0x3b1e3b4d,0xbac13a20,0xbb44bb3d,0x39a1bae4,0x39a13b11,0xbb44bae4,0xbac1bb3d,0x3b1e3a20,0xbb02bacd,0xbb35bb49,0x3a6eba9d,0x3b4c3b2a,
0xb9a1bb11,0x3b443ae4,0x3ac13b3d,0xbb1eba20,0x3b020000,0x3b353b49,0xba6e3a9d,0xbb4cbb2a,0x3b4c3b11,0x3a6e3b2a,0xbb35ba9d,0xbb02bb49,
0x3b1e3acd,0xbac13a20,0xbb44bb3d,0x39a1bae4,0x3b113acd,0xbb110000,0xbb11bb4d,0x3b110000,0x3b113b4d,0xbb110000,0xbb11bb4d,0x3b110000,
0x3b113b4d,0xbb110000,0xbb11bb4d,0x3b110000,0x3b113b4d,0xbb110000,0xbb11bb4d,0x3b110000,0xbb113acd,0xbb11bb4d,0x3b110000,0x3b113b4d,
0xbb110000,0xbb11bb4d,0x3b110000,0x3b113b4d,0xbb110000,0xbb11bb4d,0x3b110000,0x3b113b4d,0xbb110000,0xbb11bb4d,0x3b110000,0x3b113b4d,
0xb9a13b11,0xbb44bb2a,0x3ac1ba9d,0x3b1e3b49,0x3b023acd,0xbb35ba20,0xba6ebb3d,0x3b4c3ae4,0xbb4cbb11,0x3a6ebae4,0x3b353b3d,0xbb023a20,
0xbb1e0000,0xbac1bb49,0x3b443a9d,0x39a13b2a,0xbb4cbb11,0x3a6ebae4,0x3b353b3d,0xbb023a20,0xbb1ebacd,0xbac1bb49,0x3b443a9d,0x39a13b2a,
0x39a1bb11,0x3b443b2a,0xbac13a9d,0xbb1ebb49,0xbb02bb4d,0x3b353a20,0x3a6e3b3d,0xbb4cbae4,0xbae4bb4d,0x3b493a9d,0xba203b11,0xbb2abb3d,
0x3b2a0000,0x3a203b3d,0xbb49bb11,0x3ae4ba9d,0x3ae43acd,0xbb49ba9d,0x3a20bb11,0x3b2a3b3d,0xbb2a0000,0xba20bb3d,0x3b493b11,0xbae43a9d,
0x3b2a0000,0x3a203b3d,0xbb49bb11,0x3ae4ba9d,0x3ae43b4d,0xbb49ba9d,0x3a20bb11,0x3b2a3b3d,0xbb2a3acd,0xba20bb3d,0x3b493b11,0xbae43a9d,
0xbae4bb4d,0x3b493a9d,0xba203b11,0xbb2abb3d,0xba6e3b11,0xbb02bb49,0x3b4c3a9d,0xbac13ae4,0x3b350000,0xb9a13b2a,0xbb1ebb3d,0x3b443a20,
0xbb44bb11,0x3b1eba20,0x39a13b3d,0xbb35bb2a,0x3ac13acd,0xbb4cbae4,0x3b02ba9d,0x3a6e3b49,0xbb44bb11,0x3b1eba20,0x39a13b3d,0xbb35bb2a,
0x3ac13b4d,0xbb4cbae4,0x3b02ba9d,0x3a6e3b49,0x3a6ebb11,0x3b023b49,0xbb4cba9d,0x3ac1bae4,0xbb35bacd,0x39a1bb2a,0x3b1e3b3d,0xbb44ba20,
0xbb3d3acd,0x3a9dbb11,0x3a9d3b4d,0xbb3dbb11,0x3b3d0000,0xba9d3b11,0xba9dbb4d,0x3b3d3b11,0xbb3d0000,0x3a9dbb11,0x3a9d3b4d,0xbb3dbb11,
0x3b3d0000,0xba9d3b11,0xba9dbb4d,0x3b3d3b11,0x3a9d3acd,0xbb3dbb11,0x3b3d0000,0xba9d3b11,0xba9dbb4d,0x3b3d3b11,0xbb3d0000,0x3a9dbb11,
0x3a9d3b4d,0xbb3dbb11,0x3b3d0000,0xba9d3b11,0xba9dbb4d,0x3b3d3b11,0xbb3d0000,0x3a9dbb11,0x3b353b11,0xbb4cba20,0x3b1eba9d,0xba6e3b2a,
0xbb44bacd,0x3b02bae4,0xb9a13b3d,0xbac1bb49,0xbac13b11,0xb9a1bb49,0x3b023b3d,0xbb44bae4,0xba6ebb4d,0x3b1e3b2a,0xbb4cba9d,0x3b35ba20,
0x3ac1bb11,0x39a13b49,0xbb02bb3d,0x3b443ae4,0x3a6e3acd,0xbb1ebb2a,0x3b4c3a9d,0xbb353a20,0x3b353b11,0xbb4cba20,0x3b1eba9d,0xba6e3b2a,
0xbb440000,0x3b02bae4,0xb9a13b3d,0xbac1bb49,0x3b490000,0xbb2a3a9d,0x3ae4bb11,0xba203b3d,0xba20bb4d,0x3ae43b3d,0xbb2abb11,0x3b493a9d,
0xbb493acd,0x3b2aba9d,0xbae43b11,0x3a20bb3d,0x3a203b4d,0xbae4bb3d,0x3b2a3b11,0xbb49ba9d,0xba20bb4d,0x3ae43b3d,0xbb2abb11,0x3b493a9d,
0xbb490000,0x3b2aba9d,0xbae43b11,0x3a20bb3d,0x3a203acd,0xbae4bb3d,0x3b2a3b11,0xbb49ba9d,0x3b490000,0xbb2a3a9d,0x3ae4bb11,0xba203b3d,
0x3b1e3b11,0xbb35bae4,0x3b443a9d,0xbb4cba20,0x39a13b4d,0xba6ebb49,0x3ac13b3d,0xbb02bb2a,0xbb023b11,0x3ac1bb2a,0xba6e3b3d,0x39a1bb49,
0xbb4cbacd,0x3b44ba20,0xbb353a9d,0x3b1ebae4,0x3b02bb11,0xbac13b2a,0x3a6ebb3d,0xb9a13b49,0x3b4c0000,0xbb443a20,0x3b35ba9d,0xbb1e3ae4,
0x3b1e3b11,0xbb35bae4,0x3b443a9d,0xbb4cba20,0x39a13acd,0xba6ebb49,0x3ac13b3d,0xbb02bb2a,0x3acd,0xbb4d,0x3b4d,0xbb4d,
0x3b4d,0xbb4d,0x3b4d,0xbb4d,0x3b4d,0xbb4d,0x3b4d,0xbb4d,0x3b4d,0xbb4d,0x3b4d,0xbb4d,
0xbb4d3acd,0x3b4d0000,0xbb4d0000,0x3b4d0000,0xbb4d0000,0x3b4d0000,0xbb4d0000,0x3b4d0000,0xbb4d0000,0x3b4d0000,0xbb4d0000,0x3b4d0000,
0xbb4d0000,0x3b4d0000,0xbb4d0000,0x3b4d0000,0xbb1e3b11,0x3b35bae4,0xbb443a9d,0x3b4cba20,0xb9a13acd,0x3a6ebb49,0xbac13b3d,0x3b02bb2a,
0xbb02bb11,0x3ac13b2a,0xba6ebb3d,0x39a13b49,0xbb4c0000,0x3b443a20,0xbb35ba9d,0x3b1e3ae4,0xbb02bb11,0x3ac13b2a,0xba6ebb3d,0x39a13b49,
0xbb4cbacd,0x3b443a20,0xbb35ba9d,0x3b1e3ae4,0x3b1ebb11,0xbb353ae4,0x3b44ba9d,0xbb4c3a20,0x39a1bb4d,0xba6e3b49,0x3ac1bb3d,0xbb023b2a,
0x3a20bb4d,0xbae43b3d,0x3b2abb11,0xbb493a9d,0x3b490000,0xbb2aba9d,0x3ae43b11,0xba20bb3d,0xba203acd,0x3ae4bb3d,0xbb2a3b11,0x3b49ba9d,
0xbb490000,0x3b2a3a9d,0xbae4bb11,0x3a203b3d,0x3b490000,0xbb2aba9d,0x3ae43b11,0xba20bb3d,0xba203b4d,0x3ae4bb3d,0xbb2a3b11,0x3b49ba9d,
0xbb493acd,0x3b2a3a9d,0xbae4bb11,0x3a203b3d,0x3a20bb4d,0xbae43b3d,0x3b2abb11,0xbb493a9d,0xbb353b11,0x3b4cba20,0xbb1eba9d,0x3a6e3b2a,
0x3b440000,0xbb02bae4,0x39a13b3d,0x3ac1bb49,0xbac1bb11,0xb9a13b49,0x3b02bb3d,0xbb443ae4,0xba6e3acd,0x3b1ebb2a,0xbb4c3a9d,0x3b353a20,
0xbac1bb11,0xb9a13b49,0x3b02bb3d,0xbb443ae4,0xba6e3b4d,0x3b1ebb2a,0xbb4c3a9d,0x3b353a20,0x3b35bb11,0xbb4c3a20,0x3b1e3a9d,0xba6ebb2a,
0xbb44bacd,0x3b023ae4,0xb9a1bb3d,0xbac13b49,0xbb3d3acd,0x3a9d3b11,0x3a9dbb4d,0xbb3d3b11,0x3b3d0000,0xba9dbb11,0xba9d3b4d,0x3b3dbb11,
0xbb3d0000,0x3a9d3b11,0x3a9dbb4d,0xbb3d3b11,0x3b3d0000,0xba9dbb11,0xba9d3b4d,0x3b3dbb11,0xba9d3acd,0x3b3dbb11,0xbb3d0000,0x3a9d3b11,
0x3a9dbb4d,0xbb3d3b11,0x3b3d0000,0xba9dbb11,0xba9d3b4d,0x3b3dbb11,0xbb3d0000,0x3a9d3b11,0x3a9dbb4d,0xbb3d3b11,0x3b3d0000,0xba9dbb11,
0x3a6e3b11,0x3b02bb49,0xbb4c3a9d,0x3ac13ae4,0xbb35bacd,0x39a13b2a,0x3b1ebb3d,0xbb443a20,0xbb443b11,0x3b1e3a20,0x39a1bb3d,0xbb353b2a,
0x3ac1bb4d,0xbb4c3ae4,0x3b023a9d,0x3a6ebb49,0x3b44bb11,0xbb1eba20,0xb9a13b3d,0x3b35bb2a,0xbac13acd,0x3b4cbae4,0xbb02ba9d,0xba6e3b49,
0x3a6e3b11,0x3b02bb49,0xbb4c3a9d,0x3ac13ae4,0xbb350000,0x39a13b2a,0x3b1ebb3d,0xbb443a20,0x3b2a0000,0x3a20bb3d,0xbb493b11,0x3ae43a9d,
0x3ae4bb4d,0xbb493a9d,0x3a203b11,0x3b2abb3d,0xbb2a3acd,0xba203b3d,0x3b49bb11,0xbae4ba9d,0xbae43b4d,0x3b49ba9d,0xba20bb11,0xbb2a3b3d,
0x3ae4bb4d,0xbb493a9d,0x3a203b11,0x3b2abb3d,0xbb2a0000,0xba203b3d,0x3b49bb11,0xbae4ba9d,0xbae43acd,0x3b49ba9d,0xba20bb11,0xbb2a3b3d,
0x3b2a0000,0x3a20bb3d,0xbb493b11,0x3ae43a9d,0x39a13b11,0x3b44bb2a,0xbac1ba9d,0xbb1e3b49,0xbb023b4d,0x3b35ba20,0x3a6ebb3d,0xbb4c3ae4,
0xbb4c3b11,0x3a6e3ae4,0x3b35bb3d,0xbb02ba20,0xbb1ebacd,0xbac13b49,0x3b44ba9d,0x39a1bb2a,0x3b4cbb11,0xba6ebae4,0xbb353b3d,0x3b023a20,
0x3b1e0000,0x3ac1bb49,0xbb443a9d,0xb9a13b2a,0x39a13b11,0x3b44bb2a,0xbac1ba9d,0xbb1e3b49,0xbb023acd,0x3b35ba20,0x3a6ebb3d,0xbb4c3ae4,
0xbb113acd,0x3b110000,0x3b11bb4d,0xbb110000,0xbb113b4d,0x3b110000,0x3b11bb4d,0xbb110000,0xbb113b4d,0x3b110000,0x3b11bb4d,0xbb110000,
0xbb113b4d,0x3b110000,0x3b11bb4d,0xbb110000,0xbb113acd,0xbb113b4d,0x3b110000,0x3b11bb4d,0xbb110000,0xbb113b4d,0x3b110000,0x3b11bb4d,
0xbb110000,0xbb113b4d,0x3b110000,0x3b11bb4d,0xbb110000,0xbb113b4d,0x3b110000,0x3b11bb4d,0xbb4c3b11,0xba6e3b2a,0x3b35ba9d,0x3b02bb49,
0xbb1e3acd,0x3ac13a20,0x3b44bb3d,0xb9a1bae4,0x39a1bb11,0xbb443ae4,0xbac13b3d,0x3b1eba20,0xbb020000,0xbb353b49,0x3a6e3a9d,0x3b4cbb2a,
0x39a1bb11,0xbb443ae4,0xbac13b3d,0x3b1eba20,0xbb02bacd,0xbb353b49,0x3a6e3a9d,0x3b4cbb2a,0x3b4cbb11,0x3a6ebb2a,0xbb353a9d,0xbb023b49,
0x3b1ebb4d,0xbac1ba20,0xbb443b3d,0x39a13ae4,0x3b2abb4d,0xba20ba9d,0xbb493b11,0xbae43b3d,0x3ae40000,0x3b49bb3d,0x3a20bb11,0xbb2a3a9d,
0xbb2a3acd,0x3a203a9d,0x3b49bb11,0x3ae4bb3d,0xbae40000,0xbb493b3d,0xba203b11,0x3b2aba9d,0x3ae40000,0x3b49bb3d,0x3a20bb11,0xbb2a3a9d,
0xbb2a3b4d,0x3a203a9d,0x3b49bb11,0x3ae4bb3d,0xbae43acd,0xbb493b3d,0xba203b11,0x3b2aba9d,0x3b2abb4d,0xba20ba9d,0xbb493b11,0xbae43b3d,
0xbb443b11,0xbb1e3b49,0x39a13a9d,0x3b35bae4,0x3ac10000,0x3b4cbb2a,0x3b02bb3d,0xba6eba20,0x3a6ebb11,0xbb023a20,0xbb4c3b3d,0xbac13b2a,
0xbb353acd,0xb9a13ae4,0x3b1eba9d,0x3b44bb49,0x3a6ebb11,0xbb023a20,0xbb4c3b3d,0xbac13b2a,0xbb353b4d,0xb9a13ae4,0x3b1eba9d,0x3b44bb49,
0x3b44bb11,0x3b1ebb49,0xb9a1ba9d,0xbb353ae4,0xbac1bacd,0xbb4c3b2a,0xbb023b3d,0x3a6e3a20,0xba9d3acd,0xbb3d3b11,0xbb3d3b4d,0xba9d3b11,
0x3a9d0000,0x3b3dbb11,0x3b3dbb4d,0x3a9dbb11,0xba9d0000,0xbb3d3b11,0xbb3d3b4d,0xba9d3b11,0x3a9d0000,0x3b3dbb11,0x3b3dbb4d,0x3a9dbb11,
0xbb3d3acd,0xba9d3b11,0x3a9d0000,0x3b3dbb11,0x3b3dbb4d,0x3a9dbb11,0xba9d0000,0xbb3d3b11,0xbb3d3b4d,0xba9d3b11,0x3a9d0000,0x3b3dbb11,
0x3b3dbb4d,0x3a9dbb11,0xba9d0000,0xbb3d3b11,0xbac13b11,0x39a13a20,0x3b02ba9d,0x3b44bb2a,0xba6ebacd,0xbb1e3ae4,0xbb4c3b3d,0xbb353b49,
0xbb353b11,0xbb4c3b49,0xbb1e3b3d,0xba6e3ae4,0x3b44bb4d,0x3b02bb2a,0x39a1ba9d,0xbac13a20,0x3b35bb11,0x3b4cbb49,0x3b1ebb3d,0x3a6ebae4,
0xbb443acd,0xbb023b2a,0xb9a13a9d,0x3ac1ba20,0xbac13b11,0x39a13a20,0x3b02ba9d,0x3b44bb2a,0xba6e0000,0xbb1e3ae4,0xbb4c3b3d,0xbb353b49,
0x3a200000,0x3ae4ba9d,0x3b2abb11,0x3b49bb3d,0x3b49bb4d,0x3b2abb3d,0x3ae4bb11,0x3a20ba9d,0xba203acd,0xbae43a9d,0xbb2a3b11,0xbb493b3d,
0xbb493b4d,0xbb2a3b3d,0xbae43b11,0xba203a9d,0x3b49bb4d,0x3b2abb3d,0x3ae4bb11,0x3a20ba9d,0xba200000,0xbae43a9d,0xbb2a3b11,0xbb493b3d,
0xbb493acd,0xbb2a3b3d,0xbae43b11,0xba203a9d,0x3a200000,0x3ae4ba9d,0x3b2abb11,0x3b49bb3d,0xbb023b11,0xbac13ae4,0xba6e3a9d,0xb9a13a20,
0xbb4c3b4d,0xbb443b49,0xbb353b3d,0xbb1e3b2a,0xbb1e3b11,0xbb353b2a,0xbb443b3d,0xbb4c3b49,0xb9a1bacd,0xba6e3a20,0xbac13a9d,0xbb023ae4,
0x3b1ebb11,0x3b35bb2a,0x3b44bb3d,0x3b4cbb49,0x39a10000,0x3a6eba20,0x3ac1ba9d,0x3b02bae4,0xbb023b11,0xbac13ae4,0xba6e3a9d,0xb9a13a20,
0xbb4c3acd,0xbb443b49,0xbb353b3d,0xbb1e3b2a,0xbb4d3acd,0xbb4d3b4d,0xbb4d3b4d,0xbb4d3b4d,0xbb4d3b4d,0xbb4d3b4d,0xbb4d3b4d,0xbb4d3b4d,
0xbb4d3b4d,0xbb4d3b4d,0xbb4d3b4d,0xbb4d3b4d,0xbb4d3b4d,0xbb4d3b4d,0xbb4d3b4d,0xbb4d3b4d,0x3acd,0x0,0x0,0x0,
0x0,0x0,0x0,0x0,0x0,0x0,0x0,0x0,0x0,0x0,0x0,0x0,
0xbb023b11,0xbac13ae4,0xba6e3a9d,0xb9a13a20,0xbb4c3acd,0xbb443b49,0xbb353b3d,0xbb1e3b2a,0x3b1ebb11,0x3b35bb2a,0x3b44bb3d,0x3b4cbb49,
0x39a10000,0x3a6eba20,0x3ac1ba9d,0x3b02bae4,0x3b1ebb11,0x3b35bb2a,0x3b44bb3d,0x3b4cbb49,0x39a1bacd,0x3a6eba20,0x3ac1ba9d,0x3b02bae4,
0x3b02bb11,0x3ac1bae4,0x3a6eba9d,0x39a1ba20,0x3b4cbb4d,0x3b44bb49,0x3b35bb3d,0x3b1ebb2a,0x3b49bb4d,0x3b2abb3d,0x3ae4bb11,0x3a20ba9d,
0xba200000,0xbae43a9d,0xbb2a3b11,0xbb493b3d,0xbb493acd,0xbb2a3b3d,0xbae43b11,0xba203a9d,0x3a200000,0x3ae4ba9d,0x3b2abb11,0x3b49bb3d,
0xba200000,0xbae43a9d,0xbb2a3b11,0xbb493b3d,0xbb493b4d,0xbb2a3b3d,0xbae43b11,0xba203a9d,0x3a203acd,0x3ae4ba9d,0x3b2abb11,0x3b49bb3d,
0x3b49bb4d,0x3b2abb3d,0x3ae4bb11,0x3a20ba9d,0xbac13b11,0x39a13a20,0x3b02ba9d,0x3b44bb2a,0xba6e0000,0xbb1e3ae4,0xbb4c3b3d,0xbb353b49,
0x3b35bb11,0x3b4cbb49,0x3b1ebb3d,0x3a6ebae4,0xbb443acd,0xbb023b2a,0xb9a13a9d,0x3ac1ba20,0x3b35bb11,0x3b4cbb49,0x3b1ebb3d,0x3a6ebae4,
0xbb443b4d,0xbb023b2a,0xb9a13a9d,0x3ac1ba20,0x3ac1bb11,0xb9a1ba20,0xbb023a9d,0xbb443b2a,0x3a6ebacd,0x3b1ebae4,0x3b4cbb3d,0x3b35bb49,
0x3a9d3acd,0x3b3dbb11,0x3b3dbb4d,0x3a9dbb11,0xba9d0000,0xbb3d3b11,0xbb3d3b4d,0xba9d3b11,0x3a9d0000,0x3b3dbb11,0x3b3dbb4d,0x3a9dbb11,
0xba9d0000,0xbb3d3b11,0xbb3d3b4d,0xba9d3b11,0xbb3d3acd,0xba9d3b11,0x3a9d0000,0x3b3dbb11,0x3b3dbb4d,0x3a9dbb11,0xba9d0000,0xbb3d3b11,
0xbb3d3b4d,0xba9d3b11,0x3a9d0000,0x3b3dbb11,0x3b3dbb4d,0x3a9dbb11,0xba9d0000,0xbb3d3b11,0xbb443b11,0xbb1e3b49,0x39a13a9d,0x3b35bae4,
0x3ac1bacd,0x3b4cbb2a,0x3b02bb3d,0xba6eba20,0xba6e3b11,0x3b02ba20,0x3b4cbb3d,0x3ac1bb2a,0x3b35bb4d,0x39a1bae4,0xbb1e3a9d,0xbb443b49,
0x3a6ebb11,0xbb023a20,0xbb4c3b3d,0xbac13b2a,0xbb353acd,0xb9a13ae4,0x3b1eba9d,0x3b44bb49,0xbb443b11,0xbb1e3b49,0x39a13a9d,0x3b35bae4,
0x3ac10000,0x3b4cbb2a,0x3b02bb3d,0xba6eba20,0xbae40000,0xbb493b3d,0xba203b11,0x3b2aba9d,0x3b2abb4d,0xba20ba9d,0xbb493b11,0xbae43b3d,
0x3ae43acd,0x3b49bb3d,0x3a20bb11,0xbb2a3a9d,0xbb2a3b4d,0x3a203a9d,0x3b49bb11,0x3ae4bb3d,0x3b2abb4d,0xba20ba9d,0xbb493b11,0xbae43b3d,
0x3ae40000,0x3b49bb3d,0x3a20bb11,0xbb2a3a9d,0xbb2a3acd,0x3a203a9d,0x3b49bb11,0x3ae4bb3d,0xbae40000,0xbb493b3d,0xba203b11,0x3b2aba9d,
0xbb4c3b11,0xba6e3b2a,0x3b35ba9d,0x3b02bb49,0xbb1e3b4d,0x3ac13a20,0x3b44bb3d,0xb9a1bae4,0xb9a13b11,0x3b44bae4,0x3ac1bb3d,0xbb1e3a20,
0x3b02bacd,0x3b35bb49,0xba6eba9d,0xbb4c3b2a,0x39a1bb11,0xbb443ae4,0xbac13b3d,0x3b1eba20,0xbb020000,0xbb353b49,0x3a6e3a9d,0x3b4cbb2a,
0xbb4c3b11,0xba6e3b2a,0x3b35ba9d,0x3b02bb49,0xbb1e3acd,0x3ac13a20,0x3b44bb3d,0xb9a1bae4,0xbb113acd,0x3b110000,0x3b11bb4d,0xbb110000,
0xbb113b4d,0x3b110000,0x3b11bb4d,0xbb110000,0xbb113b4d,0x3b110000,0x3b11bb4d,0xbb110000,0xbb113b4d,0x3b110000,0x3b11bb4d,0xbb110000,
0x3b113acd,0x3b11bb4d,0xbb110000,0xbb113b4d,0x3b110000,0x3b11bb4d,0xbb110000,0xbb113b4d,0x3b110000,0x3b11bb4d,0xbb110000,0xbb113b4d,
0x3b110000,0x3b11bb4d,0xbb110000,0xbb113b4d,0x39a13b11,0x3b44bb2a,0xbac1ba9d,0xbb1e3b49,0xbb023acd,0x3b35ba20,0x3a6ebb3d,0xbb4c3ae4,
0x3b4cbb11,0xba6ebae4,0xbb353b3d,0x3b023a20,0x3b1e0000,0x3ac1bb49,0xbb443a9d,0xb9a13b2a,0x3b4cbb11,0xba6ebae4,0xbb353b3d,0x3b023a20,
0x3b1ebacd,0x3ac1bb49,0xbb443a9d,0xb9a13b2a,0xb9a1bb11,0xbb443b2a,0x3ac13a9d,0x3b1ebb49,0x3b02bb4d,0xbb353a20,0xba6e3b3d,0x3b4cbae4,
0x3ae4bb4d,0xbb493a9d,0x3a203b11,0x3b2abb3d,0xbb2a0000,0xba203b3d,0x3b49bb11,0xbae4ba9d,0xbae43acd,0x3b49ba9d,0xba20bb11,0xbb2a3b3d,
0x3b2a0000,0x3a20bb3d,0xbb493b11,0x3ae43a9d,0xbb2a0000,0xba203b3d,0x3b49bb11,0xbae4ba9d,0xbae43b4d,0x3b49ba9d,0xba20bb11,0xbb2a3b3d,
0x3b2a3acd,0x3a20bb3d,0xbb493b11,0x3ae43a9d,0x3ae4bb4d,0xbb493a9d,0x3a203b11,0x3b2abb3d,0x3a6e3b11,0x3b02bb49,0xbb4c3a9d,0x3ac13ae4,
0xbb350000,0x39a13b2a,0x3b1ebb3d,0xbb443a20,0x3b44bb11,0xbb1eba20,0xb9a13b3d,0x3b35bb2a,0xbac13acd,0x3b4cbae4,0xbb02ba9d,0xba6e3b49,
0x3b44bb11,0xbb1eba20,0xb9a13b3d,0x3b35bb2a,0xbac13b4d,0x3b4cbae4,0xbb02ba9d,0xba6e3b49,0xba6ebb11,0xbb023b49,0x3b4cba9d,0xbac1bae4,
0x3b35bacd,0xb9a1bb2a,0xbb1e3b3d,0x3b44ba20,0x3b3d3acd,0xba9dbb11,0xba9d3b4d,0x3b3dbb11,0xbb3d0000,0x3a9d3b11,0x3a9dbb4d,0xbb3d3b11,
0x3b3d0000,0xba9dbb11,0xba9d3b4d,0x3b3dbb11,0xbb3d0000,0x3a9d3b11,0x3a9dbb4d,0xbb3d3b11,0xba9d3acd,0x3b3dbb11,0xbb3d0000,0x3a9d3b11,
0x3a9dbb4d,0xbb3d3b11,0x3b3d0000,0xba9dbb11,0xba9d3b4d,0x3b3dbb11,0xbb3d0000,0x3a9d3b11,0x3a9dbb4d,0xbb3d3b11,0x3b3d0000,0xba9dbb11,
0xbb353b11,0x3b4cba20,0xbb1eba9d,0x3a6e3b2a,0x3b44bacd,0xbb02bae4,0x39a13b3d,0x3ac1bb49,0x3ac13b11,0x39a1bb49,0xbb023b3d,0x3b44bae4,
0x3a6ebb4d,0xbb1e3b2a,0x3b4cba9d,0xbb35ba20,0xbac1bb11,0xb9a13b49,0x3b02bb3d,0xbb443ae4,0xba6e3acd,0x3b1ebb2a,0xbb4c3a9d,0x3b353a20,
0xbb353b11,0x3b4cba20,0xbb1eba9d,0x3a6e3b2a,0x3b440000,0xbb02bae4,0x39a13b3d,0x3ac1bb49,0xbb490000,0x3b2a3a9d,0xbae4bb11,0x3a203b3d,
0x3a20bb4d,0xbae43b3d,0x3b2abb11,0xbb493a9d,0x3b493acd,0xbb2aba9d,0x3ae43b11,0xba20bb3d,0xba203b4d,0x3ae4bb3d,0xbb2a3b11,0x3b49ba9d,
0x3a20bb4d,0xbae43b3d,0x3b2abb11,0xbb493a9d,0x3b490000,0xbb2aba9d,0x3ae43b11,0xba20bb3d,0xba203acd,0x3ae4bb3d,0xbb2a3b11,0x3b49ba9d,
0xbb490000,0x3b2a3a9d,0xbae4bb11,0x3a203b3d,0xbb1e3b11,0x3b35bae4,0xbb443a9d,0x3b4cba20,0xb9a13b4d,0x3a6ebb49,0xbac13b3d,0x3b02bb2a,
0x3b023b11,0xbac1bb2a,0x3a6e3b3d,0xb9a1bb49,0x3b4cbacd,0xbb44ba20,0x3b353a9d,0xbb1ebae4,0xbb02bb11,0x3ac13b2a,0xba6ebb3d,0x39a13b49,
0xbb4c0000,0x3b443a20,0xbb35ba9d,0x3b1e3ae4,0xbb1e3b11,0x3b35bae4,0xbb443a9d,0x3b4cba20,0xb9a13acd,0x3a6ebb49,0xbac13b3d,0x3b02bb2a,
0x3acd,0xbb4d,0x3b4d,0xbb4d,0x3b4d,0xbb4d,0x3b4d,0xbb4d,0x3b4d,0xbb4d,0x3b4d,0xbb4d,
0x3b4d,0xbb4d,0x3b4d,0xbb4d,0x3b4d3acd,0xbb4d0000,0x3b4d0000,0xbb4d0000,0x3b4d0000,0xbb4d0000,0x3b4d0000,0xbb4d0000,
0x3b4d0000,0xbb4d0000,0x3b4d0000,0xbb4d0000,0x3b4d0000,0xbb4d0000,0x3b4d0000,0xbb4d0000,0x3b1e3b11,0xbb35bae4,0x3b443a9d,0xbb4cba20,
0x39a13acd,0xba6ebb49,0x3ac13b3d,0xbb02bb2a,0x3b02bb11,0xbac13b2a,0x3a6ebb3d,0xb9a13b49,0x3b4c0000,0xbb443a20,0x3b35ba9d,0xbb1e3ae4,
0x3b02bb11,0xbac13b2a,0x3a6ebb3d,0xb9a13b49,0x3b4cbacd,0xbb443a20,0x3b35ba9d,0xbb1e3ae4,0xbb1ebb11,0x3b353ae4,0xbb44ba9d,0x3b4c3a20,
0xb9a1bb4d,0x3a6e3b49,0xbac1bb3d,0x3b023b2a,0xba20bb4d,0x3ae43b3d,0xbb2abb11,0x3b493a9d,0xbb490000,0x3b2aba9d,0xbae43b11,0x3a20bb3d,
0x3a203acd,0xbae4bb3d,0x3b2a3b11,0xbb49ba9d,0x3b490000,0xbb2a3a9d,0x3ae4bb11,0xba203b3d,0xbb490000,0x3b2aba9d,0xbae43b11,0x3a20bb3d,
0x3a203b4d,0xbae4bb3d,0x3b2a3b11,0xbb49ba9d,0x3b493acd,0xbb2a3a9d,0x3ae4bb11,0xba203b3d,0xba20bb4d,0x3ae43b3d,0xbb2abb11,0x3b493a9d,
0x3b353b11,0xbb4cba20,0x3b1eba9d,0xba6e3b2a,0xbb440000,0x3b02bae4,0xb9a13b3d,0xbac1bb49,0x3ac1bb11,0x39a13b49,0xbb02bb3d,0x3b443ae4,
0x3a6e3acd,0xbb1ebb2a,0x3b4c3a9d,0xbb353a20,0x3ac1bb11,0x39a13b49,0xbb02bb3d,0x3b443ae4,0x3a6e3b4d,0xbb1ebb2a,0x3b4c3a9d,0xbb353a20,
0xbb35bb11,0x3b4c3a20,0xbb1e3a9d,0x3a6ebb2a,0x3b44bacd,0xbb023ae4,0x39a1bb3d,0x3ac13b49,0x3b3d3acd,0xba9d3b11,0xba9dbb4d,0x3b3d3b11,
0xbb3d0000,0x3a9dbb11,0x3a9d3b4d,0xbb3dbb11,0x3b3d0000,0xba9d3b11,0xba9dbb4d,0x3b3d3b11,0xbb3d0000,0x3a9dbb11,0x3a9d3b4d,0xbb3dbb11,
0x3a9d3acd,0xbb3dbb11,0x3b3d0000,0xba9d3b11,0xba9dbb4d,0x3b3d3b11,0xbb3d0000,0x3a9dbb11,0x3a9d3b4d,0xbb3dbb11,0x3b3d0000,0xba9d3b11,
0xba9dbb4d,0x3b3d3b11,0xbb3d0000,0x3a9dbb11,0xba6e3b11,0xbb02bb49,0x3b4c3a9d,0xbac13ae4,0x3b35bacd,0xb9a13b2a,0xbb1ebb3d,0x3b443a20,
0x3b443b11,0xbb1e3a20,0xb9a1bb3d,0x3b353b2a,0xbac1bb4d,0x3b4c3ae4,0xbb023a9d,0xba6ebb49,0xbb44bb11,0x3b1eba20,0x39a13b3d,0xbb35bb2a,
0x3ac13acd,0xbb4cbae4,0x3b02ba9d,0x3a6e3b49,0xba6e3b11,0xbb02bb49,0x3b4c3a9d,0xbac13ae4,0x3b350000,0xb9a13b2a,0xbb1ebb3d,0x3b443a20,
0xbb2a0000,0xba20bb3d,0x3b493b11,0xbae43a9d,0xbae4bb4d,0x3b493a9d,0xba203b11,0xbb2abb3d,0x3b2a3acd,0x3a203b3d,0xbb49bb11,0x3ae4ba9d,
0x3ae43b4d,0xbb49ba9d,0x3a20bb11,0x3b2a3b3d,0xbae4bb4d,0x3b493a9d,0xba203b11,0xbb2abb3d,0x3b2a0000,0x3a203b3d,0xbb49bb11,0x3ae4ba9d,
0x3ae43acd,0xbb49ba9d,0x3a20bb11,0x3b2a3b3d,0xbb2a0000,0xba20bb3d,0x3b493b11,0xbae43a9d,0xb9a13b11,0xbb44bb2a,0x3ac1ba9d,0x3b1e3b49,
0x3b023b4d,0xbb35ba20,0xba6ebb3d,0x3b4c3ae4,0x3b4c3b11,0xba6e3ae4,0xbb35bb3d,0x3b02ba20,0x3b1ebacd,0x3ac13b49,0xbb44ba9d,0xb9a1bb2a,
0xbb4cbb11,0x3a6ebae4,0x3b353b3d,0xbb023a20,0xbb1e0000,0xbac1bb49,0x3b443a9d,0x39a13b2a,0xb9a13b11,0xbb44bb2a,0x3ac1ba9d,0x3b1e3b49,
0x3b023acd,0xbb35ba20,0xba6ebb3d,0x3b4c3ae4,0x3b113acd,0xbb110000,0xbb11bb4d,0x3b110000,0x3b113b4d,0xbb110000,0xbb11bb4d,0x3b110000,
0x3b113b4d,0xbb110000,0xbb11bb4d,0x3b110000,0x3b113b4d,0xbb110000,0xbb11bb4d,0x3b110000,0x3b113acd,0x3b113b4d,0xbb110000,0xbb11bb4d,
0x3b110000,0x3b113b4d,0xbb110000,0xbb11bb4d,0x3b110000,0x3b113b4d,0xbb110000,0xbb11bb4d,0x3b110000,0x3b113b4d,0xbb110000,0xbb11bb4d,
0x3b4c3b11,0x3a6e3b2a,0xbb35ba9d,0xbb02bb49,0x3b1e3acd,0xbac13a20,0xbb44bb3d,0x39a1bae4,0xb9a1bb11,0x3b443ae4,0x3ac13b3d,0xbb1eba20,
0x3b020000,0x3b353b49,0xba6e3a9d,0xbb4cbb2a,0xb9a1bb11,0x3b443ae4,0x3ac13b3d,0xbb1eba20,0x3b02bacd,0x3b353b49,0xba6e3a9d,0xbb4cbb2a,
0xbb4cbb11,0xba6ebb2a,0x3b353a9d,0x3b023b49,0xbb1ebb4d,0x3ac1ba20,0x3b443b3d,0xb9a13ae4,0xbb2abb4d,0x3a20ba9d,0x3b493b11,0x3ae43b3d,
0xbae40000,0xbb49bb3d,0xba20bb11,0x3b2a3a9d,0x3b2a3acd,0xba203a9d,0xbb49bb11,0xbae4bb3d,0x3ae40000,0x3b493b3d,0x3a203b11,0xbb2aba9d,
0xbae40000,0xbb49bb3d,0xba20bb11,0x3b2a3a9d,0x3b2a3b4d,0xba203a9d,0xbb49bb11,0xbae4bb3d,0x3ae43acd,0x3b493b3d,0x3a203b11,0xbb2aba9d,
0xbb2abb4d,0x3a20ba9d,0x3b493b11,0x3ae43b3d,0x3b443b11,0x3b1e3b49,0xb9a13a9d,0xbb35bae4,0xbac10000,0xbb4cbb2a,0xbb02bb3d,0x3a6eba20,
0xba6ebb11,0x3b023a20,0x3b4c3b3d,0x3ac13b2a,0x3b353acd,0x39a13ae4,0xbb1eba9d,0xbb44bb49,0xba6ebb11,0x3b023a20,0x3b4c3b3d,0x3ac13b2a,
0x3b353b4d,0x39a13ae4,0xbb1eba9d,0xbb44bb49,0xbb44bb11,0xbb1ebb49,0x39a1ba9d,0x3b353ae4,0x3ac1bacd,0x3b4c3b2a,0x3b023b3d,0xba6e3a20,
0x3a9d3acd,0x3b3d3b11,0x3b3d3b4d,0x3a9d3b11,0xba9d0000,0xbb3dbb11,0xbb3dbb4d,0xba9dbb11,0x3a9d0000,0x3b3d3b11,0x3b3d3b4d,0x3a9d3b11,
0xba9d0000,0xbb3dbb11,0xbb3dbb4d,0xba9dbb11,0x3b3d3acd,0x3a9d3b11,0xba9d0000,0xbb3dbb11,0xbb3dbb4d,0xba9dbb11,0x3a9d0000,0x3b3d3b11,
0x3b3d3b4d,0x3a9d3b11,0xba9d0000,0xbb3dbb11,0xbb3dbb4d,0xba9dbb11,0x3a9d0000,0x3b3d3b11,0x3ac13b11,0xb9a13a20,0xbb02ba9d,0xbb44bb2a,
0x3a6ebacd,0x3b1e3ae4,0x3b4c3b3d,0x3b353b49,0x3b353b11,0x3b4c3b49,0x3b1e3b3d,0x3a6e3ae4,0xbb44bb4d,0xbb02bb2a,0xb9a1ba9d,0x3ac13a20,
0xbb35bb11,0xbb4cbb49,0xbb1ebb3d,0xba6ebae4,0x3b443acd,0x3b023b2a,0x39a13a9d,0xbac1ba20,0x3ac13b11,0xb9a13a20,0xbb02ba9d,0xbb44bb2a,
0x3a6e0000,0x3b1e3ae4,0x3b4c3b3d,0x3b353b49,0xba200000,0xbae4ba9d,0xbb2abb11,0xbb49bb3d,0xbb49bb4d,0xbb2abb3d,0xbae4bb11,0xba20ba9d,
0x3a203acd,0x3ae43a9d,0x3b2a3b11,0x3b493b3d,0x3b493b4d,0x3b2a3b3d,0x3ae43b11,0x3a203a9d,0xbb49bb4d,0xbb2abb3d,0xbae4bb11,0xba20ba9d,
0x3a200000,0x3ae43a9d,0x3b2a3b11,0x3b493b3d,0x3b493acd,0x3b2a3b3d,0x3ae43b11,0x3a203a9d,0xba200000,0xbae4ba9d,0xbb2abb11,0xbb49bb3d,
0x3b023b11,0x3ac13ae4,0x3a6e3a9d,0x39a13a20,0x3b4c3b4d,0x3b443b49,0x3b353b3d,0x3b1e3b2a,0x3b1e3b11,0x3b353b2a,0x3b443b3d,0x3b4c3b49,
0x39a1bacd,0x3a6e3a20,0x3ac13a9d,0x3b023ae4,0xbb1ebb11,0xbb35bb2a,0xbb44bb3d,0xbb4cbb49,0xb9a10000,0xba6eba20,0xbac1ba9d,0xbb02bae4,
0x3b023b11,0x3ac13ae4,0x3a6e3a9d,0x39a13a20,0x3b4c3acd,0x3b443b49,0x3b353b3d,0x3b1e3b2a,0x3b4d3b4d,0x3b4d3b4d,0x3b4d3b4d,0x3b4d3b4d,
0x3b4d3b4d,0x3b4d3b4d,0x3b4d3b4d,0x3b4d3b4d,0x3b4d3b4d,0x3b4d3b4d,0x3b4d3b4d,0x3b4d3b4d,0x3b4d3b4d,0x3b4d3b4d,0x3b4d3b4d,0x3b4d3b4d,
0x0,0x0,0x0,0x0,0x0,0x0,0x0,0x0,0x0,0x0,0x0,0x0,
0x0,0x0,0x0,0x0,0x3af43b0a,0x3aaf3ad3,0x3a473a8a,0x392139f0,0x3b4b3b4d,0x3b413b47,0x3b303b39,0x3b183b24,
0xbb24bb18,0xbb39bb30,0xbb47bb41,0xbb4dbb4b,0xb9f0b921,0xba8aba47,0xbad3baaf,0xbb0abaf4,0xbb24bb18,0xbb39bb30,0xbb47bb41,0xbb4dbb4b,
0xb9f0b921,0xba8aba47,0xbad3baaf,0xbb0abaf4,0xbaf4bb0a,0xbaafbad3,0xba47ba8a,0xb921b9f0,0xbb4bbb4d,0xbb41bb47,0xbb30bb39,0xbb18bb24,
0xbb44bb4c,0xbb1ebb35,0xbac1bb02,0xb9a1ba6e,0x3a6e39a1,0x3b023ac1,0x3b353b1e,0x3b4c3b44,0x3b443b4c,0x3b1e3b35,0x3ac13b02,0x39a13a6e,
0xba6eb9a1,0xbb02bac1,0xbb35bb1e,0xbb4cbb44,0x3a6e39a1,0x3b023ac1,0x3b353b1e,0x3b4c3b44,0x3b443b4c,0x3b1e3b35,0x3ac13b02,0x39a13a6e,
0xba6eb9a1,0xbb02bac1,0xbb35bb1e,0xbb4cbb44,0xbb44bb4c,0xbb1ebb35,0xbac1bb02,0xb9a1ba6e,0x3a8a3af4,0xba473921,0xbb18bad3,0xbb4bbb39,
0x3aaf39f0,0x3b303b0a,0x3b4d3b47,0x3b243b41,0xbb41bb24,0xbb47bb4d,0xbb0abb30,0xb9f0baaf,0x3b393b4b,0x3ad33b18,0xb9213a47,0xbaf4ba8a,
0xbb41bb24,0xbb47bb4d,0xbb0abb30,0xb9f0baaf,0x3b393b4b,0x3ad33b18,0xb9213a47,0xbaf4ba8a,0xba8abaf4,0x3a47b921,0x3b183ad3,0x3b4b3b39,
0xbaafb9f0,0xbb30bb0a,0xbb4dbb47,0xbb24bb41,0xbae4ba20,0xbb49bb2a,0xbb2abb49,0xba20bae4,0x3ae43a20,0x3b493b2a,0x3b2a3b49,0x3a203ae4,
0xbae4ba20,0xbb49bb2a,0xbb2abb49,0xba20bae4,0x3ae43a20,0x3b493b2a,0x3b2a3b49,0x3a203ae4,0x3b2a3b49,0x3a203ae4,0xbae4ba20,0xbb49bb2a,
0xbb2abb49,0xba20bae4,0x3ae43a20,0x3b493b2a,0x3b2a3b49,0x3a203ae4,0xbae4ba20,0xbb49bb2a,0xbb2abb49,0xba20bae4,0x3ae43a20,0x3b493b2a,
0x3b4d3b30,0x3af43b39,0xba8a39f0,0xbb47bb18,0xbb0aba47,0xbb4bbb41,0xbaafbb24,0x3ad33921,0x39213ad3,0xbb24baaf,0xbb41bb4b,0xba47bb0a,
0xbb18bb47,0x39f0ba8a,0x3b393af4,0x3b303b4d,0xb921bad3,0x3b243aaf,0x3b413b4b,0x3a473b0a,0x3b183b47,0xb9f03a8a,0xbb39baf4,0xbb30bb4d,
0x3b4d3b30,0x3af43b39,0xba8a39f0,0xbb47bb18,0xbb0aba47,0xbb4bbb41,0xbaafbb24,0x3ad33921,0x3b1e3a6e,0x3b353b4c,0xb9a13ac1,0xbb44bb02,
0xbb02bb44,0x3ac1b9a1,0x3b4c3b35,0x3a6e3b1e,0xbb1eba6e,0xbb35bb4c,0x39a1bac1,0x3b443b02,0x3b023b44,0xbac139a1,0xbb4cbb35,0xba6ebb1e,
0xbb02bb44,0x3ac1b9a1,0x3b4c3b35,0x3a6e3b1e,0xbb1eba6e,0xbb35bb4c,0x39a1bac1,0x3b443b02,0x3b023b44,0xbac139a1,0xbb4cbb35,0xba6ebb1e,
0x3b1e3a6e,0x3b353b4c,0xb9a13ac1,0xbb44bb02,0x3b473b39,0xb9213af4,0xbb4bbb0a,0xba8abb30,0x3ad33b41,0xbb18b9f0,0xbb24bb4d,0x3aafba47,
0xba473aaf,0xbb4dbb24,0xb9f0bb18,0x3b413ad3,0xbb30ba8a,0xbb0abb4b,0x3af4b921,0x3b393b47,0x3a47baaf,0x3b4d3b24,0x39f03b18,0xbb41bad3,
0x3b303a8a,0x3b0a3b4b,0xbaf43921,0xbb39bb47,0x3b473b39,0xb9213af4,0xbb4bbb0a,0xba8abb30,0x3ad33b41,0xbb18b9f0,0xbb24bb4d,0x3aafba47,
0x3a9d3b3d,0xbb3dba9d,0xba9dbb3d,0x3b3d3a9d,0x3a9d3b3d,0xbb3dba9d,0xba9dbb3d,0x3b3d3a9d,0x3a9d3b3d,0xbb3dba9d,0xba9dbb3d,0x3b3d3a9d,
0x3a9d3b3d,0xbb3dba9d,0xba9dbb3d,0x3b3d3a9d,0xbb3dba9d,0xba9dbb3d,0x3b3d3a9d,0x3a9d3b3d,0xbb3dba9d,0xba9dbb3d,0x3b3d3a9d,0x3a9d3b3d,
0xbb3dba9d,0xba9dbb3d,0x3b3d3a9d,0x3a9d3b3d,0xbb3dba9d,0xba9dbb3d,0x3b3d3a9d,0x3a9d3b3d,0xbad33a8a,0xbb18bb4b,0x3b243921,0x3aaf3b47,
0x3a473b39,0xbb4dbaf4,0x39f0bb0a,0x3b413b30,0xbb30bb41,0x3b0ab9f0,0x3af43b4d,0xbb39ba47,0xbb47baaf,0xb921bb24,0x3b4b3b18,0xba8a3ad3,
0xbb30bb41,0x3b0ab9f0,0x3af43b4d,0xbb39ba47,0xbb47baaf,0xb921bb24,0x3b4b3b18,0xba8a3ad3,0x3ad3ba8a,0x3b183b4b,0xbb24b921,0xbaafbb47,
0xba47bb39,0x3b4d3af4,0xb9f03b0a,0xbb41bb30,0xb9a1bb35,0x3b443b1e,0xbb023a6e,0xbac1bb4c,0x3b4c3ac1,0xba6e3b02,0xbb1ebb44,0x3b3539a1,
0x39a13b35,0xbb44bb1e,0x3b02ba6e,0x3ac13b4c,0xbb4cbac1,0x3a6ebb02,0x3b1e3b44,0xbb35b9a1,0x3b4c3ac1,0xba6e3b02,0xbb1ebb44,0x3b3539a1,
0x39a13b35,0xbb44bb1e,0x3b02ba6e,0x3ac13b4c,0xbb4cbac1,0x3a6ebb02,0x3b1e3b44,0xbb35b9a1,0xb9a1bb35,0x3b443b1e,0xbb023a6e,0xbac1bb4c,
0xbb183a47,0xb9f0bb41,0x3b393b24,0xbb303921,0x3b4d3ad3,0xbaf43aaf,0xba8abb4b,0x3b473b0a,0xbb0abb47,0x3b4b3a8a,0xbaaf3af4,0xbad3bb4d,
0xb9213b30,0xbb24bb39,0x3b4139f0,0xba473b18,0xbb0abb47,0x3b4b3a8a,0xbaaf3af4,0xbad3bb4d,0xb9213b30,0xbb24bb39,0x3b4139f0,0xba473b18,
0x3b18ba47,0x39f03b41,0xbb39bb24,0x3b30b921,0xbb4dbad3,0x3af4baaf,0x3a8a3b4b,0xbb47bb0a,0xbb49bae4,0x3b2aba20,0xba203b2a,0xbae4bb49,
0x3b493ae4,0xbb2a3a20,0x3a20bb2a,0x3ae43b49,0xbb49bae4,0x3b2aba20,0xba203b2a,0xbae4bb49,0x3b493ae4,0xbb2a3a20,0x3a20bb2a,0x3ae43b49,
0xba203b2a,0xbae4bb49,0x3b493ae4,0xbb2a3a20,0x3a20bb2a,0x3ae43b49,0xbb49bae4,0x3b2aba20,0xba203b2a,0xbae4bb49,0x3b493ae4,0xbb2a3a20,
0x3a20bb2a,0x3ae43b49,0xbb49bae4,0x3b2aba20,0x3aaf3b4b,0xbb30bb18,0x3b4d3a47,0xbb243a8a,0xbb41baf4,0x3b473921,0xbb0a3ad3,0x39f0bb39,
0xbb3939f0,0x3ad3bb0a,0x39213b47,0xbaf4bb41,0x3a8abb24,0x3a473b4d,0xbb18bb30,0x3b4b3aaf,0x3b39b9f0,0xbad33b0a,0xb921bb47,0x3af43b41,
0xba8a3b24,0xba47bb4d,0x3b183b30,0xbb4bbaaf,0x3aaf3b4b,0xbb30bb18,0x3b4d3a47,0xbb243a8a,0xbb41baf4,0x3b473921,0xbb0a3ad3,0x39f0bb39,
0x3b353b02,0xbb4cba6e,0x3b44b9a1,0xbb1e3ac1,0x3ac1bb1e,0xb9a13b44,0xba6ebb4c,0x3b023b35,0xbb35bb02,0x3b4c3a6e,0xbb4439a1,0x3b1ebac1,
0xbac13b1e,0x39a1bb44,0x3a6e3b4c,0xbb02bb35,0x3ac1bb1e,0xb9a13b44,0xba6ebb4c,0x3b023b35,0xbb35bb02,0x3b4c3a6e,0xbb4439a1,0x3b1ebac1,
0xbac13b1e,0x39a1bb44,0x3a6e3b4c,0xbb02bb35,0x3b353b02,0xbb4cba6e,0x3b44b9a1,0xbb1e3ac1,0x39f03b4d,0xba8abb47,0x3ad33b39,0xbb0abb24,
0xbaf43b18,0x3aafbb30,0xba473b41,0x3921bb4b,0xbb4b3921,0x3b41ba47,0xbb303aaf,0x3b18baf4,0xbb24bb0a,0x3b393ad3,0xbb47ba8a,0x3b4d39f0,
0x3b4bb921,0xbb413a47,0x3b30baaf,0xbb183af4,0x3b243b0a,0xbb39bad3,0x3b473a8a,0xbb4db9f0,0x39f03b4d,0xba8abb47,0x3ad33b39,0xbb0abb24,
0xbaf43b18,0x3aafbb30,0xba473b41,0x3921bb4b,0xbb113b11,0x3b11bb11,0xbb113b11,0x3b11bb11,0xbb113b11,0x3b11bb11,0xbb113b11,0x3b11bb11,
0xbb113b11,0x3b11bb11,0xbb113b11,0x3b11bb11,0xbb113b11,0x3b11bb11,0xbb113b11,0x3b11bb11,0xbb11bb11,0x3b113b11,0xbb11bb11,0x3b113b11,
0xbb11bb11,0x3b113b11,0xbb11bb11,0x3b113b11,0xbb11bb11,0x3b113b11,0xbb11bb11,0x3b113b11,0xbb11bb11,0x3b113b11,0xbb11bb11,0x3b113b11,
0xbb4bb921,0x3b413a47,0xbb30baaf,0x3b183af4,0xbb243b0a,0x3b39bad3,0xbb473a8a,0x3b4db9f0,0x39f0bb4d,0xba8a3b47,0x3ad3bb39,0xbb0a3b24,
0xbaf4bb18,0x3aaf3b30,0xba47bb41,0x39213b4b,0x39f0bb4d,0xba8a3b47,0x3ad3bb39,0xbb0a3b24,0xbaf4bb18,0x3aaf3b30,0xba47bb41,0x39213b4b,
0x3b4b3921,0xbb41ba47,0x3b303aaf,0xbb18baf4,0x3b24bb0a,0xbb393ad3,0x3b47ba8a,0xbb4d39f0,0x3b35bb02,0xbb4c3a6e,0x3b4439a1,0xbb1ebac1,
0x3ac13b1e,0xb9a1bb44,0xba6e3b4c,0x3b02bb35,0xbb353b02,0x3b4cba6e,0xbb44b9a1,0x3b1e3ac1,0xbac1bb1e,0x39a13b44,0x3a6ebb4c,0xbb023b35,
0x3ac13b1e,0xb9a1bb44,0xba6e3b4c,0x3b02bb35,0xbb353b02,0x3b4cba6e,0xbb44b9a1,0x3b1e3ac1,0xbac1bb1e,0x39a13b44,0x3a6ebb4c,0xbb023b35,
0x3b35bb02,0xbb4c3a6e,0x3b4439a1,0xbb1ebac1,0xbb39b9f0,0x3ad33b0a,0x3921bb47,0xbaf43b41,0x3a8a3b24,0x3a47bb4d,0xbb183b30,0x3b4bbaaf,
0x3aafbb4b,0xbb303b18,0x3b4dba47,0xbb24ba8a,0xbb413af4,0x3b47b921,0xbb0abad3,0x39f03b39,0x3aafbb4b,0xbb303b18,0x3b4dba47,0xbb24ba8a,
0xbb413af4,0x3b47b921,0xbb0abad3,0x39f03b39,0x3b3939f0,0xbad3bb0a,0xb9213b47,0x3af4bb41,0xba8abb24,0xba473b4d,0x3b18bb30,0xbb4b3aaf,
0xba20bb2a,0xbae43b49,0x3b49bae4,0xbb2aba20,0x3a203b2a,0x3ae4bb49,0xbb493ae4,0x3b2a3a20,0xba20bb2a,0xbae43b49,0x3b49bae4,0xbb2aba20,
0x3a203b2a,0x3ae4bb49,0xbb493ae4,0x3b2a3a20,0xbb493ae4,0x3b2a3a20,0xba20bb2a,0xbae43b49,0x3b49bae4,0xbb2aba20,0x3a203b2a,0x3ae4bb49,
0xbb493ae4,0x3b2a3a20,0xba20bb2a,0xbae43b49,0x3b49bae4,0xbb2aba20,0x3a203b2a,0x3ae4bb49,0xbb0a3b47,0x3b4bba8a,0xbaafbaf4,0xbad33b4d,
0xb921bb30,0xbb243b39,0x3b41b9f0,0xba47bb18,0xbb18ba47,0xb9f03b41,0x3b39bb24,0xbb30b921,0x3b4dbad3,0xbaf4baaf,0xba8a3b4b,0x3b47bb0a,
0x3b183a47,0x39f0bb41,0xbb393b24,0x3b303921,0xbb4d3ad3,0x3af43aaf,0x3a8abb4b,0xbb473b0a,0xbb0a3b47,0x3b4bba8a,0xbaafbaf4,0xbad33b4d,
0xb921bb30,0xbb243b39,0x3b41b9f0,0xba47bb18,0xb9a13b35,0x3b44bb1e,0xbb02ba6e,0xbac13b4c,0x3b4cbac1,0xba6ebb02,0xbb1e3b44,0x3b35b9a1,
0x39a1bb35,0xbb443b1e,0x3b023a6e,0x3ac1bb4c,0xbb4c3ac1,0x3a6e3b02,0x3b1ebb44,0xbb3539a1,0x3b4cbac1,0xba6ebb02,0xbb1e3b44,0x3b35b9a1,
0x39a1bb35,0xbb443b1e,0x3b023a6e,0x3ac1bb4c,0xbb4c3ac1,0x3a6e3b02,0x3b1ebb44,0xbb3539a1,0xb9a13b35,0x3b44bb1e,0xbb02ba6e,0xbac13b4c,
0xbb303b41,0x3b0a39f0,0x3af4bb4d,0xbb393a47,0xbb473aaf,0xb9213b24,0x3b4bbb18,0xba8abad3,0xbad3ba8a,0xbb183b4b,0x3b24b921,0x3aafbb47,
0x3a47bb39,0xbb4d3af4,0x39f03b0a,0x3b41bb30,0x3ad33a8a,0x3b18bb4b,0xbb243921,0xbaaf3b47,0xba473b39,0x3b4dbaf4,0xb9f0bb0a,0xbb413b30,
0xbb303b41,0x3b0a39f0,0x3af4bb4d,0xbb393a47,0xbb473aaf,0xb9213b24,0x3b4bbb18,0xba8abad3,0xbb3d3a9d,0xba9d3b3d,0x3b3dba9d,0x3a9dbb3d,
0xbb3d3a9d,0xba9d3b3d,0x3b3dba9d,0x3a9dbb3d,0xbb3d3a9d,0xba9d3b3d,0x3b3dba9d,0x3a9dbb3d,0xbb3d3a9d,0xba9d3b3d,0x3b3dba9d,0x3a9dbb3d,
0x3a9dbb3d,0xbb3d3a9d,0xba9d3b3d,0x3b3dba9d,0x3a9dbb3d,0xbb3d3a9d,0xba9d3b3d,0x3b3dba9d,0x3a9dbb3d,0xbb3d3a9d,0xba9d3b3d,0x3b3dba9d,
0x3a9dbb3d,0xbb3d3a9d,0xba9d3b3d,0x3b3dba9d,0xba47baaf,0xbb4d3b24,0xb9f03b18,0x3b41bad3,0xbb303a8a,0xbb0a3b4b,0x3af43921,0x3b39bb47,
0x3b47bb39,0xb921baf4,0xbb4b3b0a,0xba8a3b30,0x3ad3bb41,0xbb1839f0,0xbb243b4d,0x3aaf3a47,0x3b47bb39,0xb921baf4,0xbb4b3b0a,0xba8a3b30,
0x3ad3bb41,0xbb1839f0,0xbb243b4d,0x3aaf3a47,0x3a473aaf,0x3b4dbb24,0x39f0bb18,0xbb413ad3,0x3b30ba8a,0x3b0abb4b,0xbaf4b921,0xbb393b47,
0x3b1eba6e,0x3b35bb4c,0xb9a1bac1,0xbb443b02,0xbb023b44,0x3ac139a1,0x3b4cbb35,0x3a6ebb1e,0xbb1e3a6e,0xbb353b4c,0x39a13ac1,0x3b44bb02,
0x3b02bb44,0xbac1b9a1,0xbb4c3b35,0xba6e3b1e,0xbb023b44,0x3ac139a1,0x3b4cbb35,0x3a6ebb1e,0xbb1e3a6e,0xbb353b4c,0x39a13ac1,0x3b44bb02,
0x3b02bb44,0xbac1b9a1,0xbb4c3b35,0xba6e3b1e,0x3b1eba6e,0x3b35bb4c,0xb9a1bac1,0xbb443b02,0x3921bad3,0xbb243aaf,0xbb413b4b,0xba473b0a,
0xbb183b47,0x39f03a8a,0x3b39baf4,0x3b30bb4d,0x3b4dbb30,0x3af4bb39,0xba8ab9f0,0xbb473b18,0xbb0a3a47,0xbb4b3b41,0xbaaf3b24,0x3ad3b921,
0x3b4dbb30,0x3af4bb39,0xba8ab9f0,0xbb473b18,0xbb0a3a47,0xbb4b3b41,0xbaaf3b24,0x3ad3b921,0xb9213ad3,0x3b24baaf,0x3b41bb4b,0x3a47bb0a,
0x3b18bb47,0xb9f0ba8a,0xbb393af4,0xbb303b4d,0x3b2abb49,0x3a20bae4,0xbae43a20,0xbb493b2a,0xbb2a3b49,0xba203ae4,0x3ae4ba20,0x3b49bb2a,
0x3b2abb49,0x3a20bae4,0xbae43a20,0xbb493b2a,0xbb2a3b49,0xba203ae4,0x3ae4ba20,0x3b49bb2a,0xbae43a20,0xbb493b2a,0xbb2a3b49,0xba203ae4,
0x3ae4ba20,0x3b49bb2a,0x3b2abb49,0x3a20bae4,0xbae43a20,0xbb493b2a,0xbb2a3b49,0xba203ae4,0x3ae4ba20,0x3b49bb2a,0x3b2abb49,0x3a20bae4,
0xbb413b24,0xbb473b4d,0xbb0a3b30,0xb9f03aaf,0x3b39bb4b,0x3ad3bb18,0xb921ba47,0xbaf43a8a,0x3a8abaf4,0xba47b921,0xbb183ad3,0xbb4b3b39,
0x3aafb9f0,0x3b30bb0a,0x3b4dbb47,0x3b24bb41,0xba8a3af4,0x3a473921,0x3b18bad3,0x3b4bbb39,0xbaaf39f0,0xbb303b0a,0xbb4d3b47,0xbb243b41,
0xbb413b24,0xbb473b4d,0xbb0a3b30,0xb9f03aaf,0x3b39bb4b,0x3ad3bb18,0xb921ba47,0xbaf43a8a,0xbb443b4c,0xbb1e3b35,0xbac13b02,0xb9a13a6e,
0x3a6eb9a1,0x3b02bac1,0x3b35bb1e,0x3b4cbb44,0x3b44bb4c,0x3b1ebb35,0x3ac1bb02,0x39a1ba6e,0xba6e39a1,0xbb023ac1,0xbb353b1e,0xbb4c3b44,
0x3a6eb9a1,0x3b02bac1,0x3b35bb1e,0x3b4cbb44,0x3b44bb4c,0x3b1ebb35,0x3ac1bb02,0x39a1ba6e,0xba6e39a1,0xbb023ac1,0xbb353b1e,0xbb4c3b44,
0xbb443b4c,0xbb1e3b35,0xbac13b02,0xb9a13a6e,0xbb243b18,0xbb393b30,0xbb473b41,0xbb4d3b4b,0xb9f03921,0xba8a3a47,0xbad33aaf,0xbb0a3af4,
0x3af4bb0a,0x3aafbad3,0x3a47ba8a,0x3921b9f0,0x3b4bbb4d,0x3b41bb47,0x3b30bb39,0x3b18bb24,0xbaf43b0a,0xbaaf3ad3,0xba473a8a,0xb92139f0,
0xbb4b3b4d,0xbb413b47,0xbb303b39,0xbb183b24,0xbb243b18,0xbb393b30,0xbb473b41,0xbb4d3b4b,0xb9f03921,0xba8a3a47,0xbad33aaf,0xbb0a3af4,
0x0,0x0,0x0,0x0,0x0,0x0,0x0,0x0,0x0,0x0,0x0,0x0,
0x0,0x0,0x0,0x0,0x3b4dbb4d,0x3b4dbb4d,0x3b4dbb4d,0x3b4dbb4d,0x3b4dbb4d,0x3b4dbb4d,0x3b4dbb4d,0x3b4dbb4d,
0x3b4dbb4d,0x3b4dbb4d,0x3b4dbb4d,0x3b4dbb4d,0x3b4dbb4d,0x3b4dbb4d,0x3b4dbb4d,0x3b4dbb4d,0x3b24bb18,0x3b39bb30,0x3b47bb41,0x3b4dbb4b,
0x39f0b921,0x3a8aba47,0x3ad3baaf,0x3b0abaf4,0x3af4bb0a,0x3aafbad3,0x3a47ba8a,0x3921b9f0,0x3b4bbb4d,0x3b41bb47,0x3b30bb39,0x3b18bb24,
0x3af4bb0a,0x3aafbad3,0x3a47ba8a,0x3921b9f0,0x3b4bbb4d,0x3b41bb47,0x3b30bb39,0x3b18bb24,0xbb243b18,0xbb393b30,0xbb473b41,0xbb4d3b4b,
0xb9f03921,0xba8a3a47,0xbad33aaf,0xbb0a3af4,0xba6e39a1,0xbb023ac1,0xbb353b1e,0xbb4c3b44,0xbb443b4c,0xbb1e3b35,0xbac13b02,0xb9a13a6e,
0x3a6eb9a1,0x3b02bac1,0x3b35bb1e,0x3b4cbb44,0x3b44bb4c,0x3b1ebb35,0x3ac1bb02,0x39a1ba6e,0xbb443b4c,0xbb1e3b35,0xbac13b02,0xb9a13a6e,
0x3a6eb9a1,0x3b02bac1,0x3b35bb1e,0x3b4cbb44,0x3b44bb4c,0x3b1ebb35,0x3ac1bb02,0x39a1ba6e,0xba6e39a1,0xbb023ac1,0xbb353b1e,0xbb4c3b44,
0x3b41bb24,0x3b47bb4d,0x3b0abb30,0x39f0baaf,0xbb393b4b,0xbad33b18,0x39213a47,0x3af4ba8a,0x3a8abaf4,0xba47b921,0xbb183ad3,0xbb4b3b39,
0x3aafb9f0,0x3b30bb0a,0x3b4dbb47,0x3b24bb41,0x3a8abaf4,0xba47b921,0xbb183ad3,0xbb4b3b39,0x3aafb9f0,0x3b30bb0a,0x3b4dbb47,0x3b24bb41,
0xbb413b24,0xbb473b4d,0xbb0a3b30,0xb9f03aaf,0x3b39bb4b,0x3ad3bb18,0xb921ba47,0xbaf43a8a,0x3b2abb49,0x3a20bae4,0xbae43a20,0xbb493b2a,
0xbb2a3b49,0xba203ae4,0x3ae4ba20,0x3b49bb2a,0x3b2abb49,0x3a20bae4,0xbae43a20,0xbb493b2a,0xbb2a3b49,0xba203ae4,0x3ae4ba20,0x3b49bb2a,
0x3ae4ba20,0x3b49bb2a,0x3b2abb49,0x3a20bae4,0xbae43a20,0xbb493b2a,0xbb2a3b49,0xba203ae4,0x3ae4ba20,0x3b49bb2a,0x3b2abb49,0x3a20bae4,
0xbae43a20,0xbb493b2a,0xbb2a3b49,0xba203ae4,0xb9213ad3,0x3b24baaf,0x3b41bb4b,0x3a47bb0a,0x3b18bb47,0xb9f0ba8a,0xbb393af4,0xbb303b4d,
0x3b4dbb30,0x3af4bb39,0xba8ab9f0,0xbb473b18,0xbb0a3a47,0xbb4b3b41,0xbaaf3b24,0x3ad3b921,0xbb4d3b30,0xbaf43b39,0x3a8a39f0,0x3b47bb18,
0x3b0aba47,0x3b4bbb41,0x3aafbb24,0xbad33921,0xb9213ad3,0x3b24baaf,0x3b41bb4b,0x3a47bb0a,0x3b18bb47,0xb9f0ba8a,0xbb393af4,0xbb303b4d,
0xbb023b44,0x3ac139a1,0x3b4cbb35,0x3a6ebb1e,0xbb1e3a6e,0xbb353b4c,0x39a13ac1,0x3b44bb02,0x3b02bb44,0xbac1b9a1,0xbb4c3b35,0xba6e3b1e,
0x3b1eba6e,0x3b35bb4c,0xb9a1bac1,0xbb443b02,0xbb1e3a6e,0xbb353b4c,0x39a13ac1,0x3b44bb02,0x3b02bb44,0xbac1b9a1,0xbb4c3b35,0xba6e3b1e,
0x3b1eba6e,0x3b35bb4c,0xb9a1bac1,0xbb443b02,0xbb023b44,0x3ac139a1,0x3b4cbb35,0x3a6ebb1e,0x3a473aaf,0x3b4dbb24,0x39f0bb18,0xbb413ad3,
0x3b30ba8a,0x3b0abb4b,0xbaf4b921,0xbb393b47,0x3b47bb39,0xb921baf4,0xbb4b3b0a,0xba8a3b30,0x3ad3bb41,0xbb1839f0,0xbb243b4d,0x3aaf3a47,
0xbb473b39,0x39213af4,0x3b4bbb0a,0x3a8abb30,0xbad33b41,0x3b18b9f0,0x3b24bb4d,0xbaafba47,0x3a473aaf,0x3b4dbb24,0x39f0bb18,0xbb413ad3,
0x3b30ba8a,0x3b0abb4b,0xbaf4b921,0xbb393b47,0x3b3dba9d,0x3a9dbb3d,0xbb3d3a9d,0xba9d3b3d,0x3b3dba9d,0x3a9dbb3d,0xbb3d3a9d,0xba9d3b3d,
0x3b3dba9d,0x3a9dbb3d,0xbb3d3a9d,0xba9d3b3d,0x3b3dba9d,0x3a9dbb3d,0xbb3d3a9d,0xba9d3b3d,0x3a9dbb3d,0xbb3d3a9d,0xba9d3b3d,0x3b3dba9d,
0x3a9dbb3d,0xbb3d3a9d,0xba9d3b3d,0x3b3dba9d,0x3a9dbb3d,0xbb3d3a9d,0xba9d3b3d,0x3b3dba9d,0x3a9dbb3d,0xbb3d3a9d,0xba9d3b3d,0x3b3dba9d,
0x3b30bb41,0xbb0ab9f0,0xbaf43b4d,0x3b39ba47,0x3b47baaf,0x3921bb24,0xbb4b3b18,0x3a8a3ad3,0xbad3ba8a,0xbb183b4b,0x3b24b921,0x3aafbb47,
0x3a47bb39,0xbb4d3af4,0x39f03b0a,0x3b41bb30,0xbad3ba8a,0xbb183b4b,0x3b24b921,0x3aafbb47,0x3a47bb39,0xbb4d3af4,0x39f03b0a,0x3b41bb30,
0xbb303b41,0x3b0a39f0,0x3af4bb4d,0xbb393a47,0xbb473aaf,0xb9213b24,0x3b4bbb18,0xba8abad3,0xbb4c3ac1,0x3a6e3b02,0x3b1ebb44,0xbb3539a1,
0xb9a13b35,0x3b44bb1e,0xbb02ba6e,0xbac13b4c,0x3b4cbac1,0xba6ebb02,0xbb1e3b44,0x3b35b9a1,0x39a1bb35,0xbb443b1e,0x3b023a6e,0x3ac1bb4c,
0xb9a13b35,0x3b44bb1e,0xbb02ba6e,0xbac13b4c,0x3b4cbac1,0xba6ebb02,0xbb1e3b44,0x3b35b9a1,0x39a1bb35,0xbb443b1e,0x3b023a6e,0x3ac1bb4c,
0xbb4c3ac1,0x3a6e3b02,0x3b1ebb44,0xbb3539a1,0x3b0abb47,0xbb4b3a8a,0x3aaf3af4,0x3ad3bb4d,0x39213b30,0x3b24bb39,0xbb4139f0,0x3a473b18,
0xbb18ba47,0xb9f03b41,0x3b39bb24,0xbb30b921,0x3b4dbad3,0xbaf4baaf,0xba8a3b4b,0x3b47bb0a,0xbb18ba47,0xb9f03b41,0x3b39bb24,0xbb30b921,
0x3b4dbad3,0xbaf4baaf,0xba8a3b4b,0x3b47bb0a,0xbb0a3b47,0x3b4bba8a,0xbaafbaf4,0xbad33b4d,0xb921bb30,0xbb243b39,0x3b41b9f0,0xba47bb18,
0xba20bb2a,0xbae43b49,0x3b49bae4,0xbb2aba20,0x3a203b2a,0x3ae4bb49,0xbb493ae4,0x3b2a3a20,0xba20bb2a,0xbae43b49,0x3b49bae4,0xbb2aba20,
0x3a203b2a,0x3ae4bb49,0xbb493ae4,0x3b2a3a20,0x3b49bae4,0xbb2aba20,0x3a203b2a,0x3ae4bb49,0xbb493ae4,0x3b2a3a20,0xba20bb2a,0xbae43b49,
0x3b49bae4,0xbb2aba20,0x3a203b2a,0x3ae4bb49,0xbb493ae4,0x3b2a3a20,0xba20bb2a,0xbae43b49,0x3b3939f0,0xbad3bb0a,0xb9213b47,0x3af4bb41,
0xba8abb24,0xba473b4d,0x3b18bb30,0xbb4b3aaf,0x3aafbb4b,0xbb303b18,0x3b4dba47,0xbb24ba8a,0xbb413af4,0x3b47b921,0xbb0abad3,0x39f03b39,
0xbaaf3b4b,0x3b30bb18,0xbb4d3a47,0x3b243a8a,0x3b41baf4,0xbb473921,0x3b0a3ad3,0xb9f0bb39,0x3b3939f0,0xbad3bb0a,0xb9213b47,0x3af4bb41,
0xba8abb24,0xba473b4d,0x3b18bb30,0xbb4b3aaf,0x3ac13b1e,0xb9a1bb44,0xba6e3b4c,0x3b02bb35,0xbb353b02,0x3b4cba6e,0xbb44b9a1,0x3b1e3ac1,
0xbac1bb1e,0x39a13b44,0x3a6ebb4c,0xbb023b35,0x3b35bb02,0xbb4c3a6e,0x3b4439a1,0xbb1ebac1,0xbb353b02,0x3b4cba6e,0xbb44b9a1,0x3b1e3ac1,
0xbac1bb1e,0x39a13b44,0x3a6ebb4c,0xbb023b35,0x3b35bb02,0xbb4c3a6e,0x3b4439a1,0xbb1ebac1,0x3ac13b1e,0xb9a1bb44,0xba6e3b4c,0x3b02bb35,
0x3b4b3921,0xbb41ba47,0x3b303aaf,0xbb18baf4,0x3b24bb0a,0xbb393ad3,0x3b47ba8a,0xbb4d39f0,0x39f0bb4d,0xba8a3b47,0x3ad3bb39,0xbb0a3b24,
0xbaf4bb18,0x3aaf3b30,0xba47bb41,0x39213b4b,0xb9f03b4d,0x3a8abb47,0xbad33b39,0x3b0abb24,0x3af43b18,0xbaafbb30,0x3a473b41,0xb921bb4b,
0x3b4b3921,0xbb41ba47,0x3b303aaf,0xbb18baf4,0x3b24bb0a,0xbb393ad3,0x3b47ba8a,0xbb4d39f0,0x3b11bb11,0xbb113b11,0x3b11bb11,0xbb113b11,
0x3b11bb11,0xbb113b11,0x3b11bb11,0xbb113b11,0x3b11bb11,0xbb113b11,0x3b11bb11,0xbb113b11,0x3b11bb11,0xbb113b11,0x3b11bb11,0xbb113b11,
0xbb11bb11,0x3b113b11,0xbb11bb11,0x3b113b11,0xbb11bb11,0x3b113b11,0xbb11bb11,0x3b113b11,0xbb11bb11,0x3b113b11,0xbb11bb11,0x3b113b11,
0xbb11bb11,0x3b113b11,0xbb11bb11,0x3b113b11,0xb9f0bb4d,0x3a8a3b47,0xbad3bb39,0x3b0a3b24,0x3af4bb18,0xbaaf3b30,0x3a47bb41,0xb9213b4b,
0xbb4b3921,0x3b41ba47,0xbb303aaf,0x3b18baf4,0xbb24bb0a,0x3b393ad3,0xbb47ba8a,0x3b4d39f0,0xbb4b3921,0x3b41ba47,0xbb303aaf,0x3b18baf4,
0xbb24bb0a,0x3b393ad3,0xbb47ba8a,0x3b4d39f0,0x39f03b4d,0xba8abb47,0x3ad33b39,0xbb0abb24,0xbaf43b18,0x3aafbb30,0xba473b41,0x3921bb4b,
0xbac13b1e,0x39a1bb44,0x3a6e3b4c,0xbb02bb35,0x3b353b02,0xbb4cba6e,0x3b44b9a1,0xbb1e3ac1,0x3ac1bb1e,0xb9a13b44,0xba6ebb4c,0x3b023b35,
0xbb35bb02,0x3b4c3a6e,0xbb4439a1,0x3b1ebac1,0x3b353b02,0xbb4cba6e,0x3b44b9a1,0xbb1e3ac1,0x3ac1bb1e,0xb9a13b44,0xba6ebb4c,0x3b023b35,
0xbb35bb02,0x3b4c3a6e,0xbb4439a1,0x3b1ebac1,0xbac13b1e,0x39a1bb44,0x3a6e3b4c,0xbb02bb35,0xbaafbb4b,0x3b303b18,0xbb4dba47,0x3b24ba8a,
0x3b413af4,0xbb47b921,0x3b0abad3,0xb9f03b39,0xbb3939f0,0x3ad3bb0a,0x39213b47,0xbaf4bb41,0x3a8abb24,0x3a473b4d,0xbb18bb30,0x3b4b3aaf,
0xbb3939f0,0x3ad3bb0a,0x39213b47,0xbaf4bb41,0x3a8abb24,0x3a473b4d,0xbb18bb30,0x3b4b3aaf,0x3aaf3b4b,0xbb30bb18,0x3b4d3a47,0xbb243a8a,
0xbb41baf4,0x3b473921,0xbb0a3ad3,0x39f0bb39,0xbb49bae4,0x3b2aba20,0xba203b2a,0xbae4bb49,0x3b493ae4,0xbb2a3a20,0x3a20bb2a,0x3ae43b49,
0xbb49bae4,0x3b2aba20,0xba203b2a,0xbae4bb49,0x3b493ae4,0xbb2a3a20,0x3a20bb2a,0x3ae43b49,0x3a20bb2a,0x3ae43b49,0xbb49bae4,0x3b2aba20,
0xba203b2a,0xbae4bb49,0x3b493ae4,0xbb2a3a20,0x3a20bb2a,0x3ae43b49,0xbb49bae4,0x3b2aba20,0xba203b2a,0xbae4bb49,0x3b493ae4,0xbb2a3a20,
0x3b18ba47,0x39f03b41,0xbb39bb24,0x3b30b921,0xbb4dbad3,0x3af4baaf,0x3a8a3b4b,0xbb47bb0a,0xbb0abb47,0x3b4b3a8a,0xbaaf3af4,0xbad3bb4d,
0xb9213b30,0xbb24bb39,0x3b4139f0,0xba473b18,0x3b0a3b47,0xbb4bba8a,0x3aafbaf4,0x3ad33b4d,0x3921bb30,0x3b243b39,0xbb41b9f0,0x3a47bb18,
0x3b18ba47,0x39f03b41,0xbb39bb24,0x3b30b921,0xbb4dbad3,0x3af4baaf,0x3a8a3b4b,0xbb47bb0a,0x3b4c3ac1,0xba6e3b02,0xbb1ebb44,0x3b3539a1,
0x39a13b35,0xbb44bb1e,0x3b02ba6e,0x3ac13b4c,0xbb4cbac1,0x3a6ebb02,0x3b1e3b44,0xbb35b9a1,0xb9a1bb35,0x3b443b1e,0xbb023a6e,0xbac1bb4c,
0x39a13b35,0xbb44bb1e,0x3b02ba6e,0x3ac13b4c,0xbb4cbac1,0x3a6ebb02,0x3b1e3b44,0xbb35b9a1,0xb9a1bb35,0x3b443b1e,0xbb023a6e,0xbac1bb4c,
0x3b4c3ac1,0xba6e3b02,0xbb1ebb44,0x3b3539a1,0x3ad3ba8a,0x3b183b4b,0xbb24b921,0xbaafbb47,0xba47bb39,0x3b4d3af4,0xb9f03b0a,0xbb41bb30,
0xbb30bb41,0x3b0ab9f0,0x3af43b4d,0xbb39ba47,0xbb47baaf,0xb921bb24,0x3b4b3b18,0xba8a3ad3,0x3b303b41,0xbb0a39f0,0xbaf4bb4d,0x3b393a47,
0x3b473aaf,0x39213b24,0xbb4bbb18,0x3a8abad3,0x3ad3ba8a,0x3b183b4b,0xbb24b921,0xbaafbb47,0xba47bb39,0x3b4d3af4,0xb9f03b0a,0xbb41bb30,
0xba9dbb3d,0x3b3d3a9d,0x3a9d3b3d,0xbb3dba9d,0xba9dbb3d,0x3b3d3a9d,0x3a9d3b3d,0xbb3dba9d,0xba9dbb3d,0x3b3d3a9d,0x3a9d3b3d,0xbb3dba9d,
0xba9dbb3d,0x3b3d3a9d,0x3a9d3b3d,0xbb3dba9d,0xbb3dba9d,0xba9dbb3d,0x3b3d3a9d,0x3a9d3b3d,0xbb3dba9d,0xba9dbb3d,0x3b3d3a9d,0x3a9d3b3d,
0xbb3dba9d,0xba9dbb3d,0x3b3d3a9d,0x3a9d3b3d,0xbb3dba9d,0xba9dbb3d,0x3b3d3a9d,0x3a9d3b3d,0xbb47bb39,0x3921baf4,0x3b4b3b0a,0x3a8a3b30,
0xbad3bb41,0x3b1839f0,0x3b243b4d,0xbaaf3a47,0xba473aaf,0xbb4dbb24,0xb9f0bb18,0x3b413ad3,0xbb30ba8a,0xbb0abb4b,0x3af4b921,0x3b393b47,
0xba473aaf,0xbb4dbb24,0xb9f0bb18,0x3b413ad3,0xbb30ba8a,0xbb0abb4b,0x3af4b921,0x3b393b47,0x3b473b39,0xb9213af4,0xbb4bbb0a,0xba8abb30,
0x3ad33b41,0xbb18b9f0,0xbb24bb4d,0x3aafba47,0x3b023b44,0xbac139a1,0xbb4cbb35,0xba6ebb1e,0x3b1e3a6e,0x3b353b4c,0xb9a13ac1,0xbb44bb02,
0xbb02bb44,0x3ac1b9a1,0x3b4c3b35,0x3a6e3b1e,0xbb1eba6e,0xbb35bb4c,0x39a1bac1,0x3b443b02,0x3b1e3a6e,0x3b353b4c,0xb9a13ac1,0xbb44bb02,
0xbb02bb44,0x3ac1b9a1,0x3b4c3b35,0x3a6e3b1e,0xbb1eba6e,0xbb35bb4c,0x39a1bac1,0x3b443b02,0x3b023b44,0xbac139a1,0xbb4cbb35,0xba6ebb1e,
0xbb4dbb30,0xbaf4bb39,0x3a8ab9f0,0x3b473b18,0x3b0a3a47,0x3b4b3b41,0x3aaf3b24,0xbad3b921,0x39213ad3,0xbb24baaf,0xbb41bb4b,0xba47bb0a,
0xbb18bb47,0x39f0ba8a,0x3b393af4,0x3b303b4d,0x39213ad3,0xbb24baaf,0xbb41bb4b,0xba47bb0a,0xbb18bb47,0x39f0ba8a,0x3b393af4,0x3b303b4d,
0x3b4d3b30,0x3af43b39,0xba8a39f0,0xbb47bb18,0xbb0aba47,0xbb4bbb41,0xbaafbb24,0x3ad33921,0xbae4ba20,0xbb49bb2a,0xbb2abb49,0xba20bae4,
0x3ae43a20,0x3b493b2a,0x3b2a3b49,0x3a203ae4,0xbae4ba20,0xbb49bb2a,0xbb2abb49,0xba20bae4,0x3ae43a20,0x3b493b2a,0x3b2a3b49,0x3a203ae4,
0xbb2abb49,0xba20bae4,0x3ae43a20,0x3b493b2a,0x3b2a3b49,0x3a203ae4,0xbae4ba20,0xbb49bb2a,0xbb2abb49,0xba20bae4,0x3ae43a20,0x3b493b2a,
0x3b2a3b49,0x3a203ae4,0xbae4ba20,0xbb49bb2a,0xba8abaf4,0x3a47b921,0x3b183ad3,0x3b4b3b39,0xbaafb9f0,0xbb30bb0a,0xbb4dbb47,0xbb24bb41,
0xbb41bb24,0xbb47bb4d,0xbb0abb30,0xb9f0baaf,0x3b393b4b,0x3ad33b18,0xb9213a47,0xbaf4ba8a,0x3b413b24,0x3b473b4d,0x3b0a3b30,0x39f03aaf,
0xbb39bb4b,0xbad3bb18,0x3921ba47,0x3af43a8a,0xba8abaf4,0x3a47b921,0x3b183ad3,0x3b4b3b39,0xbaafb9f0,0xbb30bb0a,0xbb4dbb47,0xbb24bb41,
0x3a6e39a1,0x3b023ac1,0x3b353b1e,0x3b4c3b44,0x3b443b4c,0x3b1e3b35,0x3ac13b02,0x39a13a6e,0xba6eb9a1,0xbb02bac1,0xbb35bb1e,0xbb4cbb44,
0xbb44bb4c,0xbb1ebb35,0xbac1bb02,0xb9a1ba6e,0x3b443b4c,0x3b1e3b35,0x3ac13b02,0x39a13a6e,0xba6eb9a1,0xbb02bac1,0xbb35bb1e,0xbb4cbb44,
0xbb44bb4c,0xbb1ebb35,0xbac1bb02,0xb9a1ba6e,0x3a6e39a1,0x3b023ac1,0x3b353b1e,0x3b4c3b44,0xbaf4bb0a,0xbaafbad3,0xba47ba8a,0xb921b9f0,
0xbb4bbb4d,0xbb41bb47,0xbb30bb39,0xbb18bb24,0xbb24bb18,0xbb39bb30,0xbb47bb41,0xbb4dbb4b,0xb9f0b921,0xba8aba47,0xbad3baaf,0xbb0abaf4,
0x3b243b18,0x3b393b30,0x3b473b41,0x3b4d3b4b,0x39f03921,0x3a8a3a47,0x3ad33aaf,0x3b0a3af4,0xbaf4bb0a,0xbaafbad3,0xba47ba8a,0xb921b9f0,
0xbb4bbb4d,0xbb41bb47,0xbb30bb39,0xbb18bb24,
};
__device__ __align__(128) const uint32_t T_tw640[512] = {
0x3f800000,0x80000000,0x3f7ffcd7,0xbc20d8d2,0x3f7ff35e,0xbca0d6d6,0x3f7fe394,0xbcf13d4c,0x3f7fcd79,0xbd20cee7,0x3f7fb10f,0xbd48fb30,
0x3f7f8e56,0xbd712283,0x3f7f654e,0xbd8ca1f2,0x3f7f35f9,0xbda0af2a,0x3f7f0059,0xbdb4b86a,0x3f7ec46d,0xbdc8bd36,0x3f7e8238,0xbddcbd0d,
0x3f7e39bc,0xbdf0b772,0x3f7deafa,0xbe0255f4,0x3f7d95f4,0xbe0c4cf7,0x3f7d3aac,0xbe164083,0x3f7cd925,0xbe20305b,0x3f7c7160,0xbe2a1c3f,
0x3f7c0361,0xbe3403f1,0x3f7b8f2a,0xbe3de731,0x3f7b14be,0xbe47c5c2,0x3f7a9421,0xbe519f65,0x3f7a0d54,0xbe5b73dc,0x3f79805c,0xbe6542e9,
0x3f78ed3c,0xbe6f0c4d,0x3f7853f8,0xbe78cfcc,0x3f77b493,0xbe814693,0x3f770f11,0xbe862210,0x3f766377,0xbe8afa3e,0x3f75b1c9,0xbe8fcefe,
0x3f74fa0b,0xbe94a031,0x3f743c41,0xbe996dba,0x3f737871,0xbe9e377a,0x3f72ae9e,0xbea2fd52,0x3f71decf,0xbea7bf25,0x3f710908,0xbeac7cd4,
0x3f702d4f,0xbeb13641,0x3f6f4ba8,0xbeb5eb4f,0x3f6e641a,0xbeba9be1,0x3f6d76aa,0xbebf47d7,0x3f6c835e,0xbec3ef15,0x3f6b8a3d,0xbec8917e,
0x3f6a8b4b,0xbecd2ef3,0x3f698690,0xbed1c759,0x3f687c12,0xbed65a92,0x3f676bd8,0xbedae880,0x3f6655e7,0xbedf7108,0x3f653a48,0xbee3f40d,
0x3f641901,0xbee87171,0x3f62f219,0xbeece91a,0x3f61c598,0xbef15aea,0x3f609384,0xbef5c6c5,0x3f5f5be6,0xbefa2c90,0x3f5e1ec5,0xbefe8c2f,
0x3f5cdc29,0xbf0172c3,0x3f5b941a,0xbf039c3d,0x3f5a46a0,0xbf05c277,0x3f58f3c4,0xbf07e565,0x3f579b8c,0xbf0a04f8,0x3f563e03,0xbf0c2124,
0x3f54db31,0xbf0e39da,0x3f53731f,0xbf104f0e,0x3f5205d4,0xbf1260b2,0x3f50935b,0xbf146eba,0x3f800000,0x80000000,0x3f7ff35e,0xbca0d6d6,
0x3f7fcd79,0xbd20cee7,0x3f7f8e56,0xbd712283,0x3f7f35f9,0xbda0af2a,0x3f7ec46d,0xbdc8bd36,0x3f7e39bc,0xbdf0b772,0x3f7d95f4,0xbe0c4cf7,
0x3f7cd925,0xbe20305b,0x3f7c0361,0xbe3403f1,0x3f7b14be,0xbe47c5c2,0x3f7a0d54,0xbe5b73dc,0x3f78ed3c,0xbe6f0c4d,0x3f77b493,0xbe814693,
0x3f766377,0xbe8afa3e,0x3f74fa0b,0xbe94a031,0x3f737871,0xbe9e377a,0x3f71decf,0xbea7bf25,0x3f702d4f,0xbeb13641,0x3f6e641a,0xbeba9be1,
0x3f6c835e,0xbec3ef15,0x3f6a8b4b,0xbecd2ef3,0x3f687c12,0xbed65a92,0x3f6655e7,0xbedf7108,0x3f641901,0xbee87171,0x3f61c598,0xbef15aea,
0x3f5f5be6,0xbefa2c90,0x3f5cdc29,0xbf0172c3,0x3f5a46a0,0xbf05c277,0x3f579b8c,0xbf0a04f8,0x3f54db31,0xbf0e39da,0x3f5205d4,0xbf1260b2,
0x3f4f1bbd,0xbf167918,0x3f4c1d35,0xbf1a82a4,0x3f490a88,0xbf1e7cf1,0x3f45e403,0xbf226799,0x3f42a9f7,0xbf26423a,0x3f3f5cb5,0xbf2a0c73,
0x3f3bfc8f,0xbf2dc5e3,0x3f3889dc,0xbf316e2c,0x3f3504f3,0xbf3504f3,0x3f316e2c,0xbf3889dc,0x3f2dc5e3,0xbf3bfc8f,0x3f2a0c73,0xbf3f5cb5,
0x3f26423a,0xbf42a9f7,0x3f226799,0xbf45e403,0x3f1e7cf1,0xbf490a88,0x3f1a82a4,0xbf4c1d35,0x3f167918,0xbf4f1bbd,0x3f1260b2,0xbf5205d4,
0x3f0e39da,0xbf54db31,0x3f0a04f8,0xbf579b8c,0x3f05c277,0xbf5a46a0,0x3f0172c3,0xbf5cdc29,0x3efa2c90,0xbf5f5be6,0x3ef15aea,0xbf61c598,
0x3ee87171,0xbf641901,0x3edf7108,0xbf6655e7,0x3ed65a92,0xbf687c12,0x3ecd2ef3,0xbf6a8b4b,0x3ec3ef15,0xbf6c835e,0x3eba9be1,0xbf6e641a,
0x3eb13641,0xbf702d4f,0x3ea7bf25,0xbf71decf,0x3f800000,0x80000000,0x3f7fe394,0xbcf13d4c,0x3f7f8e56,0xbd712283,0x3f7f0059,0xbdb4b86a,
0x3f7e39bc,0xbdf0b772,0x3f7d3aac,0xbe164083,0x3f7c0361,0xbe3403f1,0x3f7a9421,0xbe519f65,0x3f78ed3c,0xbe6f0c4d,0x3f770f11,0xbe862210,
0x3f74fa0b,0xbe94a031,0x3f72ae9e,0xbea2fd52,0x3f702d4f,0xbeb13641,0x3f6d76aa,0xbebf47d7,0x3f6a8b4b,0xbecd2ef3,0x3f676bd8,0xbedae880,
0x3f641901,0xbee87171,0x3f609384,0xbef5c6c5,0x3f5cdc29,0xbf0172c3,0x3f58f3c4,0xbf07e565,0x3f54db31,0xbf0e39da,0x3f50935b,0xbf146eba,
0x3f4c1d35,0xbf1a82a4,0x3f4779bc,0xbf207440,0x3f42a9f7,0xbf26423a,0x3f3daef9,0xbf2beb4a,0x3f3889dc,0xbf316e2c,0x3f333bc6,0xbf36c9a9,
0x3f2dc5e3,0xbf3bfc8f,0x3f28296a,0xbf4105b8,0x3f226799,0xbf45e403,0x3f1c81b9,0xbf4a965e,0x3f167918,0xbf4f1bbd,0x3f104f0e,0xbf53731f,
0x3f0a04f8,0xbf579b8c,0x3f039c3d,0xbf5b941a,0x3efa2c90,0xbf5f5be6,0x3eece91a,0xbf62f219,0x3edf7108,0xbf6655e7,0x3ed1c759,0xbf698690,
0x3ec3ef15,0xbf6c835e,0x3eb5eb4f,0xbf6f4ba8,0x3ea7bf25,0xbf71decf,0x3e996dba,0xbf743c41,0x3e8afa3e,0xbf766377,0x3e78cfcc,0xbf7853f8,
0x3e5b73dc,0xbf7a0d54,0x3e3de731,0xbf7b8f2a,0x3e20305b,0xbf7cd925,0x3e0255f4,0xbf7deafa,0x3dc8bd36,0xbf7ec46d,0x3d8ca1f2,0xbf7f654e,
0x3d20cee7,0xbf7fcd79,0x3c20d8d2,0xbf7ffcd7,0xbca0d6d6,0xbf7ff35e,0xbd48fb30,0xbf7fb10f,0xbda0af2a,0xbf7f35f9,0xbddcbd0d,0xbf7e8238,
0xbe0c4cf7,0xbf7d95f4,0xbe2a1c3f,0xbf7c7160,0xbe47c5c2,0xbf7b14be,0xbe6542e9,0xbf79805c,0xbe814693,0xbf77b493,0xbe8fcefe,0xbf75b1c9,
0x3f800000,0x80000000,0x3f7fcd79,0xbd20cee7,0x3f7f35f9,0xbda0af2a,0x3f7e39bc,0xbdf0b772,0x3f7cd925,0xbe20305b,0x3f7b14be,0xbe47c5c2,
0x3f78ed3c,0xbe6f0c4d,0x3f766377,0xbe8afa3e,0x3f737871,0xbe9e377a,0x3f702d4f,0xbeb13641,0x3f6c835e,0xbec3ef15,0x3f687c12,0xbed65a92,
0x3f641901,0xbee87171,0x3f5f5be6,0xbefa2c90,0x3f5a46a0,0xbf05c277,0x3f54db31,0xbf0e39da,0x3f4f1bbd,0xbf167918,0x3f490a88,0xbf1e7cf1,
0x3f42a9f7,0xbf26423a,0x3f3bfc8f,0xbf2dc5e3,0x3f3504f3,0xbf3504f3,0x3f2dc5e3,0xbf3bfc8f,0x3f26423a,0xbf42a9f7,0x3f1e7cf1,0xbf490a88,
0x3f167918,0xbf4f1bbd,0x3f0e39da,0xbf54db31,0x3f05c277,0xbf5a46a0,0x3efa2c90,0xbf5f5be6,0x3ee87171,0xbf641901,0x3ed65a92,0xbf687c12,
0x3ec3ef15,0xbf6c835e,0x3eb13641,0xbf702d4f,0x3e9e377a,0xbf737871,0x3e8afa3e,0xbf766377,0x3e6f0c4d,0xbf78ed3c,0x3e47c5c2,0xbf7b14be,
0x3e20305b,0xbf7cd925,0x3df0b772,0xbf7e39bc,0x3da0af2a,0xbf7f35f9,0x3d20cee7,0xbf7fcd79,0x248d3132,0xbf800000,0xbd20cee7,0xbf7fcd79,
0xbda0af2a,0xbf7f35f9,0xbdf0b772,0xbf7e39bc,0xbe20305b,0xbf7cd925,0xbe47c5c2,0xbf7b14be,0xbe6f0c4d,0xbf78ed3c,0xbe8afa3e,0xbf766377,
0xbe9e377a,0xbf737871,0xbeb13641,0xbf702d4f,0xbec3ef15,0xbf6c835e,0xbed65a92,0xbf687c12,0xbee87171,0xbf641901,0xbefa2c90,0xbf5f5be6,
0xbf05c277,0xbf5a46a0,0xbf0e39da,0xbf54db31,0xbf167918,0xbf4f1bbd,0xbf1e7cf1,0xbf490a88,0xbf26423a,0xbf42a9f7,0xbf2dc5e3,0xbf3bfc8f,
0xbf3504f3,0xbf3504f3,0xbf3bfc8f,0xbf2dc5e3,0xbf42a9f7,0xbf26423a,0xbf490a88,0xbf1e7cf1,
};
__device__ __align__(128) const uint32_t T_tw2048[4096] = {
0x3f800000,0x80000000,0x3f800000,0x80000000,0x3f800000,0x80000000,0x3f800000,0x80000000,0x3f800000,0x80000000,0x3f800000,0x80000000,
0x3f800000,0x80000000,0x3f800000,0x80000000,0x3f800000,0x80000000,0x3f7fffb1,0xbb490fc6,0x3f7ffec4,0xbbc90f88,0x3f7ffd39,0xbc16cb58,
0x3f7ffb11,0xbc490e90,0x3f7ff84a,0xbc7b514b,0x3f7ff4e6,0xbc96c9b6,0x3f7ff0e3,0xbcafea69,0x3f800000,0x80000000,0x3f7ffec4,0xbbc90f88,
0x3f7ffb11,0xbc490e90,0x3f7ff4e6,0xbc96c9b6,0x3f7fec43,0xbcc90ab0,0x3f7fe129,0xbcfb49ba,0x3f7fd397,0xbd16c32c,0x3f7fc38f,0xbd2fe007,
0x3f800000,0x80000000,0x3f7ffd39,0xbc16cb58,0x3f7ff4e6,0xbc96c9b6,0x3f7fe705,0xbce22a7a,0x3f7fd397,0xbd16c32c,0x3f7fba9e,0xbd3c6dd5,
0x3f7f9c18,0xbd621469,0x3f7f7808,0xbd83db0a,0x3f800000,0x80000000,0x3f7ffb11,0xbc490e90,0x3f7fec43,0xbcc90ab0,0x3f7fd397,0xbd16c32c,
0x3f7fb10f,0xbd48fb30,0x3f7f84ab,0xbd7b2b74,0x3f7f4e6d,0xbd96a905,0x3f7f0e58,0xbdafb680,0x3f800000,0x80000000,0x3f7ff84a,0xbc7b514b,
0x3f7fe129,0xbcfb49ba,0x3f7fba9e,0xbd3c6dd5,0x3f7f84ab,0xbd7b2b74,0x3f7f3f54,0xbd9cecf9,0x3f7eea9d,0xbdbc3ac3,0x3f7e868b,0xbddb7d37,
0x3f800000,0x80000000,0x3f7ff4e6,0xbc96c9b6,0x3f7fd397,0xbd16c32c,0x3f7f9c18,0xbd621469,0x3f7f4e6d,0xbd96a905,0x3f7eea9d,0xbdbc3ac3,
0x3f7e70b0,0xbde1bc2e,0x3f7de0b1,0xbe039502,0x3f800000,0x80000000,0x3f7ff0e3,0xbcafea69,0x3f7fc38f,0xbd2fe007,0x3f7f7808,0xbd83db0a,
0x3f7f0e58,0xbdafb680,0x3f7e868b,0xbddb7d37,0x3f7de0b1,0xbe039502,0x3f7d1cdd,0xbe195be0,0x3f800000,0x80000000,0x3f800000,0x80000000,
0x3f800000,0x80000000,0x3f800000,0x80000000,0x3f800000,0x80000000,0x3f800000,0x80000000,0x3f800000,0x80000000,0x3f800000,0x80000000,
0x3f7fec43,0xbcc90ab0,0x3f7fe705,0xbce22a7a,0x3f7fe129,0xbcfb49ba,0x3f7fdaaf,0xbd0a342f,0x3f7fd397,0xbd16c32c,0x3f7fcbe2,0xbd2351cb,
0x3f7fc38f,0xbd2fe007,0x3f7fba9e,0xbd3c6dd5,0x3f7fb10f,0xbd48fb30,0x3f7f9c18,0xbd621469,0x3f7f84ab,0xbd7b2b74,0x3f7f6ac7,0xbd8a200a,
0x3f7f4e6d,0xbd96a905,0x3f7f2f9d,0xbda3308c,0x3f7f0e58,0xbdafb680,0x3f7eea9d,0xbdbc3ac3,0x3f7f4e6d,0xbd96a905,0x3f7f1f49,0xbda973ba,
0x3f7eea9d,0xbdbc3ac3,0x3f7eb069,0xbdcefdb7,0x3f7e70b0,0xbde1bc2e,0x3f7e2b72,0xbdf475c0,0x3f7de0b1,0xbe039502,0x3f7d906e,0xbe0cec4a,
0x3f7ec46d,0xbdc8bd36,0x3f7e70b0,0xbde1bc2e,0x3f7e1324,0xbdfab273,0x3f7dabcc,0xbe09cf86,0x3f7d3aac,0xbe164083,0x3f7cbfc9,0xbe22abb6,
0x3f7c3b28,0xbe2f10a2,0x3f7baccd,0xbe3b6ecf,0x3f7e1324,0xbdfab273,0x3f7d906e,0xbe0cec4a,0x3f7cfe73,0xbe1c76de,0x3f7c5d3a,0xbe2bf804,
0x3f7baccd,0xbe3b6ecf,0x3f7aed37,0xbe4ada4f,0x3f7a1e84,0xbe5a3997,0x3f7940c0,0xbe698bba,0x3f7d3aac,0xbe164083,0x3f7c7eb0,0xbe28defc,
0x3f7baccd,0xbe3b6ecf,0x3f7ac516,0xbe4dee60,0x3f79c79d,0xbe605c13,0x3f78b47b,0xbe72b651,0x3f778bc5,0xbe827dc0,0x3f764d97,0xbe8b9507,
0x3f7c3b28,0xbe2f10a2,0x3f7b3bab,0xbe44b0b9,0x3f7a1e84,0xbe5a3997,0x3f78e3d6,0xbe6fa8b2,0x3f778bc5,0xbe827dc0,0x3f76167a,0xbe8d17c0,
0x3f748422,0xbe97a117,0x3f72d4eb,0xbea21887,0x3f800000,0x80000000,0x3f800000,0x80000000,0x3f800000,0x80000000,0x3f800000,0x80000000,
0x3f800000,0x80000000,0x3f800000,0x80000000,0x3f800000,0x80000000,0x3f800000,0x80000000,0x3f7fb10f,0xbd48fb30,0x3f7fa6e3,0xbd55880e,
0x3f7f9c18,0xbd621469,0x3f7f90b1,0xbd6ea038,0x3f7f84ab,0xbd7b2b74,0x3f7f7808,0xbd83db0a,0x3f7f6ac7,0xbd8a200a,0x3f7f5ce9,0xbd9064b4,
0x3f7ec46d,0xbdc8bd36,0x3f7e9bc9,0xbdd53db9,0x3f7e70b0,0xbde1bc2e,0x3f7e4323,0xbdee3876,0x3f7e1324,0xbdfab273,0x3f7de0b1,0xbe039502,
0x3f7dabcc,0xbe09cf86,0x3f7d7474,0xbe1008b7,0x3f7d3aac,0xbe164083,0x3f7cdf6c,0xbe1f917b,0x3f7c7eb0,0xbe28defc,0x3f7c187a,0xbe3228d4,
0x3f7baccd,0xbe3b6ecf,0x3f7b3bab,0xbe44b0b9,0x3f7ac516,0xbe4dee60,0x3f7a4910,0xbe57278f,0x3f7b14be,0xbe47c5c2,0x3f7a7302,0xbe541501,
0x3f79c79d,0xbe605c13,0x3f791298,0xbe6c9a7f,0x3f7853f8,0xbe78cfcc,0x3f778bc5,0xbe827dc0,0x3f76ba07,0xbe888e93,0x3f75dec6,0xbe8e9a22,
0x3f7853f8,0xbe78cfcc,0x3f77583a,0xbe840270,0x3f764d97,0xbe8b9507,0x3f75341d,0xbe931f35,0x3f740bdd,0xbe9aa086,0x3f72d4eb,0xbea21887,
0x3f718f57,0xbea986c4,0x3f703b37,0xbeb0eacb,0x3f74fa0b,0xbe94a031,0x3f73913f,0xbe9d9e78,0x3f721352,0xbea68f12,0x3f708066,0xbeaf713a,
0x3f6ed89e,0xbeb8442a,0x3f6d1c1d,0xbec1071e,0x3f6b4b0c,0xbec9b953,0x3f696591,0xbed25a09,0x3f710908,0xbeac7cd4,0x3f6f20b0,0xbeb6ccc3,
0x3f6d1c1d,0xbec1071e,0x3f6afb8c,0xbecb2aae,0x3f68bf3c,0xbed53641,0x3f666771,0xbedf28a9,0x3f63f473,0xbee900b7,0x3f61668a,0xbef2bd43,
0x3f800000,0x80000000,0x3f800000,0x80000000,0x3f800000,0x80000000,0x3f800000,0x80000000,0x3f800000,0x80000000,0x3f800000,0x80000000,
0x3f800000,0x80000000,0x3f800000,0x80000000,0x3f7f4e6d,0xbd96a905,0x3f7f3f54,0xbd9cecf9,0x3f7f2f9d,0xbda3308c,0x3f7f1f49,0xbda973ba,
0x3f7f0e58,0xbdafb680,0x3f7efcc9,0xbdb5f8da,0x3f7eea9d,0xbdbc3ac3,0x3f7ed7d4,0xbdc27c39,0x3f7d3aac,0xbe164083,0x3f7cfe73,0xbe1c76de,
0x3f7cbfc9,0xbe22abb6,0x3f7c7eb0,0xbe28defc,0x3f7c3b28,0xbe2f10a2,0x3f7bf531,0xbe354098,0x3f7baccd,0xbe3b6ecf,0x3f7b61fc,0xbe419b37,
0x3f79c79d,0xbe605c13,0x3f7940c0,0xbe698bba,0x3f78b47b,0xbe72b651,0x3f7822d1,0xbe7bdba4,0x3f778bc5,0xbe827dc0,0x3f76ef5b,0xbe870ada,
0x3f764d97,0xbe8b9507,0x3f75a67b,0xbe901c2c,0x3f74fa0b,0xbe94a031,0x3f740bdd,0xbe9aa086,0x3f731447,0xbea09ae5,0x3f721352,0xbea68f12,
0x3f710908,0xbeac7cd4,0x3f6ff573,0xbeb263ef,0x3f6ed89e,0xbeb8442a,0x3f6db293,0xbebe1d4a,0x3f6ed89e,0xbeb8442a,0x3f6d67a1,0xbebf926f,
0x3f6be858,0xbec6d529,0x3f6a5ad9,0xbece0bea,0x3f68bf3c,0xbed53641,0x3f671599,0xbedc53c1,0x3f655e0b,0xbee363fa,0x3f6398ac,0xbeea6681,
0x3f676bd8,0xbedae880,0x3f655e0b,0xbee363fa,0x3f633c5a,0xbeebcbbb,0x3f6106f2,0xbef41f07,0x3f5ebe05,0xbefc5d27,0x3f5c61c7,0xbf0242b1,
0x3f59f26a,0xbf064b82,0x3f577026,0xbf0a48ad,0x3f5ebe05,0xbefc5d27,0x3f5bfb34,0xbf02ef9f,0x3f591e6a,0xbf07a136,0x3f5627fe,0xbf0c42c9,
0x3f531849,0xbf10d3cd,0x3f4fefa8,0xbf1553b7,0x3f4cae79,0xbf19c200,0x3f495521,0xbf1e1e22,0x3f800000,0x80000000,0x3f800000,0x80000000,
0x3f800000,0x80000000,0x3f800000,0x80000000,0x3f800000,0x80000000,0x3f800000,0x80000000,0x3f800000,0x80000000,0x3f800000,0x80000000,
0x3f7ec46d,0xbdc8bd36,0x3f7eb069,0xbdcefdb7,0x3f7e9bc9,0xbdd53db9,0x3f7e868b,0xbddb7d37,0x3f7e70b0,0xbde1bc2e,0x3f7e5a38,0xbde7fa9a,
0x3f7e4323,0xbdee3876,0x3f7e2b72,0xbdf475c0,0x3f7b14be,0xbe47c5c2,0x3f7ac516,0xbe4dee60,0x3f7a7302,0xbe541501,0x3f7a1e84,0xbe5a3997,
0x3f79c79d,0xbe605c13,0x3f796e4e,0xbe667c66,0x3f791298,0xbe6c9a7f,0x3f78b47b,0xbe72b651,0x3f74fa0b,0xbe94a031,0x3f74484b,0xbe9920fe,
0x3f73913f,0xbe9d9e78,0x3f72d4eb,0xbea21887,0x3f721352,0xbea68f12,0x3f714c7a,0xbeab0201,0x3f708066,0xbeaf713a,0x3f6faf1b,0xbeb3dca5,
0x3f6c835e,0xbec3ef15,0x3f6b4b0c,0xbec9b953,0x3f6a09a7,0xbecf7bca,0x3f68bf3c,0xbed53641,0x3f676bd8,0xbedae880,0x3f660f88,0xbee0924f,
0x3f64aa59,0xbee63375,0x3f633c5a,0xbeebcbbb,0x3f61c598,0xbef15aea,0x3f5fe4e9,0xbef840c8,0x3f5df6be,0xbeff17b2,0x3f5bfb34,0xbf02ef9f,
0x3f59f26a,0xbf064b82,0x3f57dc7f,0xbf099f4e,0x3f55b993,0xbf0cead0,0x3f5389c7,0xbf102dd5,0x3f54db31,0xbf0e39da,0x3f5233c6,0xbf121eb0,
0x3f4f7a1f,0xbf15f6d9,0x3f4cae79,0xbf19c200,0x3f49d112,0xbf1d7fd1,0x3f46e22a,0xbf212ff9,0x3f43e200,0xbf24d225,0x3f40d0da,0xbf286605,
0x3f45e403,0xbf226799,0x3f425b89,0xbf269de3,0x3f3ebc1b,0xbf2ac082,0x3f3b0629,0xbf2ecef7,0x3f373a23,0xbf32c8c9,0x3f33587a,0xbf36ad7f,
0x3f2f61a5,0xbf3a7ca4,0x3f2b561b,0xbf3e35c5,0x3f800000,0x80000000,0x3f800000,0x80000000,0x3f800000,0x80000000,0x3f800000,0x80000000,
0x3f800000,0x80000000,0x3f800000,0x80000000,0x3f800000,0x80000000,0x3f800000,0x80000000,0x3f7e1324,0xbdfab273,0x3f7dfa38,0xbe007745,
0x3f7de0b1,0xbe039502,0x3f7dc68c,0xbe06b26e,0x3f7dabcc,0xbe09cf86,0x3f7d906e,0xbe0cec4a,0x3f7d7474,0xbe1008b7,0x3f7d57de,0xbe1324ca,
0x3f7853f8,0xbe78cfcc,0x3f77f110,0xbe7ee6e1,0x3f778bc5,0xbe827dc0,0x3f772417,0xbe8586ce,0x3f76ba07,0xbe888e93,0x3f764d97,0xbe8b9507,
0x3f75dec6,0xbe8e9a22,0x3f756d97,0xbe919ddd,0x3f6ed89e,0xbeb8442a,0x3f6dfcf2,0xbebca7af,0x3f6d1c1d,0xbec1071e,0x3f6c3624,0xbec5625c,
0x3f6b4b0c,0xbec9b953,0x3f6a5ad9,0xbece0bea,0x3f696591,0xbed25a09,0x3f686b39,0xbed6a399,0x3f61c598,0xbef15aea,0x3f604621,0xbef6e0cb,
0x3f5ebe05,0xbefc5d27,0x3f5d2d53,0xbf00e7e4,0x3f5b941a,0xbf039c3d,0x3f59f26a,0xbf064b82,0x3f584853,0xbf08f59b,0x3f5695e5,0xbf0b9a6b,
0x3f514d3d,0xbf13682a,0x3f4f0417,0xbf16999f,0x3f4cae79,0xbf19c200,0x3f4a4c87,0xbf1ce11f,0x3f47de65,0xbf1ff6cb,0x3f456439,0xbf2302d3,
0x3f42de29,0xbf26050a,0x3f404c5c,0xbf28fd41,0x3f3daef9,0xbf2beb4a,0x3f3a7ca4,0xbf2f61a5,0x3f373a23,0xbf32c8c9,0x3f33e7bc,0xbf36206c,
0x3f3085bb,0xbf396842,0x3f2d1469,0xbf3ca003,0x3f299415,0xbf3fc767,0x3f26050a,0xbf42de29,0x3f273656,0xbf41d870,0x3f2302d3,0xbf456439,
0x3f1ebc12,0xbf48d8b3,0x3f1a6293,0xbf4c3578,0x3f15f6d9,0xbf4f7a1f,0x3f11796b,0xbf52a649,0x3f0cead0,0xbf55b993,0x3f084b92,0xbf58b3a1,
0x3f800000,0x80000000,0x3f800000,0x80000000,0x3f800000,0x80000000,0x3f800000,0x80000000,0x3f800000,0x80000000,0x3f800000,0x80000000,
0x3f800000,0x80000000,0x3f800000,0x80000000,0x3f7d3aac,0xbe164083,0x3f7d1cdd,0xbe195be0,0x3f7cfe73,0xbe1c76de,0x3f7cdf6c,0xbe1f917b,
0x3f7cbfc9,0xbe22abb6,0x3f7c9f8a,0xbe25c58c,0x3f7c7eb0,0xbe28defc,0x3f7c5d3a,0xbe2bf804,0x3f74fa0b,0xbe94a031,0x3f748422,0xbe97a117,
0x3f740bdd,0xbe9aa086,0x3f73913f,0xbe9d9e78,0x3f731447,0xbea09ae5,0x3f7294f8,0xbea395c5,0x3f721352,0xbea68f12,0x3f718f57,0xbea986c4,
0x3f676bd8,0xbedae880,0x3f666771,0xbedf28a9,0x3f655e0b,0xbee363fa,0x3f644fac,0xbee79a5d,0x3f633c5a,0xbeebcbbb,0x3f62241a,0xbeeff7fb,
0x3f6106f2,0xbef41f07,0x3f5fe4e9,0xbef840c8,0x3f54db31,0xbf0e39da,0x3f531849,0xbf10d3cd,0x3f514d3d,0xbf13682a,0x3f4f7a1f,0xbf15f6d9,
0x3f4d9f02,0xbf187fc0,0x3f4bbbf8,0xbf1b02c6,0x3f49d112,0xbf1d7fd1,0x3f47de65,0xbf1ff6cb,0x3f3daef9,0xbf2beb4a,0x3f3b0629,0xbf2ecef7,
0x3f385216,0xbf31a81d,0x3f3592e7,0xbf34768f,0x3f32c8c9,0xbf373a23,0x3f2ff3e6,0xbf39f2ac,0x3f2d1469,0xbf3ca003,0x3f2a2a80,0xbf3f41fc,
0x3f226799,0xbf45e403,0x3f1ebc12,0xbf48d8b3,0x3f1b02c6,0xbf4bbbf8,0x3f173c07,0xbf4e8d90,0x3f13682a,0xbf514d3d,0x3f0f8784,0xbf53fac3,
0x3f0b9a6b,0xbf5695e5,0x3f07a136,0xbf591e6a,0x3f039c3d,0xbf5b941a,0x3efdbabb,0xbf5e5aa6,0x3ef41f07,0xbf6106f2,0x3eea6681,0xbf6398ac,
0x3ee0924f,0xbf660f88,0x3ed6a399,0xbf686b39,0x3ecc9b8b,0xbf6aab7b,0x3ec27b55,0xbf6cd007,0x3f800000,0x80000000,0x3f800000,0x80000000,
0x3f800000,0x80000000,0x3f800000,0x80000000,0x3f800000,0x80000000,0x3f800000,0x80000000,0x3f800000,0x80000000,0x3f800000,0x80000000,
0x3f7c3b28,0xbe2f10a2,0x3f7c187a,0xbe3228d4,0x3f7bf531,0xbe354098,0x3f7bd14d,0xbe3857ec,0x3f7baccd,0xbe3b6ecf,0x3f7b87b2,0xbe3e853e,
0x3f7b61fc,0xbe419b37,0x3f7b3bab,0xbe44b0b9,0x3f710908,0xbeac7cd4,0x3f708066,0xbeaf713a,0x3f6ff573,0xbeb263ef,0x3f6f6830,0xbeb554ec,
0x3f6ed89e,0xbeb8442a,0x3f6e46be,0xbebb31a0,0x3f6db293,0xbebe1d4a,0x3f6d1c1d,0xbec1071e,0x3f5ebe05,0xbefc5d27,0x3f5d924d,0xbf003a06,
0x3f5c61c7,0xbf0242b1,0x3f5b2c79,0xbf044889,0x3f59f26a,0xbf064b82,0x3f58b3a1,0xbf084b92,0x3f577026,0xbf0a48ad,0x3f5627fe,0xbf0c42c9,
0x3f45e403,0xbf226799,0x3f43e200,0xbf24d225,0x3f41d870,0xbf273656,0x3f3fc767,0xbf299415,0x3f3daef9,0xbf2beb4a,0x3f3b8f3b,0xbf2e3bde,
0x3f396842,0xbf3085bb,0x3f373a23,0xbf32c8c9,0x3f273656,0xbf41d870,0x3f24381a,0xbf446337,0x3f212ff9,0xbf46e22a,0x3f1e1e22,0xbf495521,
0x3f1b02c6,0xbf4bbbf8,0x3f17de12,0xbf4e1689,0x3f14b039,0xbf5064af,0x3f11796b,0xbf52a649,0x3f039c3d,0xbf5b941a,0x3eff17b2,0xbf5df6be,
0x3ef6e0cb,0xbf604621,0x3eee9479,0xbf628210,0x3ee63375,0xbf64aa59,0x3eddbe79,0xbf66becc,0x3ed53641,0xbf68bf3c,0x3ecc9b8b,0xbf6aab7b,
0x3eb8442a,0xbf6ed89e,0x3eadf73c,0xbf70c501,0x3ea395c5,0xbf7294f8,0x3e9920fe,0xbf74484b,0x3e8e9a22,0xbf75dec6,0x3e840270,0xbf77583a,
0x3e72b651,0xbf78b47b,0x3e5d4b1a,0xbf79f35e,0x3f800000,0x80000000,0x3f7fec43,0xbcc90ab0,0x3f7fb10f,0xbd48fb30,0x3f7f4e6d,0xbd96a905,
0x3f7ec46d,0xbdc8bd36,0x3f7e1324,0xbdfab273,0x3f7d3aac,0xbe164083,0x3f7c3b28,0xbe2f10a2,0x3f800000,0x80000000,0x3f7fe705,0xbce22a7a,
0x3f7f9c18,0xbd621469,0x3f7f1f49,0xbda973ba,0x3f7e70b0,0xbde1bc2e,0x3f7d906e,0xbe0cec4a,0x3f7c7eb0,0xbe28defc,0x3f7b3bab,0xbe44b0b9,
0x3f800000,0x80000000,0x3f7fe129,0xbcfb49ba,0x3f7f84ab,0xbd7b2b74,0x3f7eea9d,0xbdbc3ac3,0x3f7e1324,0xbdfab273,0x3f7cfe73,0xbe1c76de,
0x3f7baccd,0xbe3b6ecf,0x3f7a1e84,0xbe5a3997,0x3f800000,0x80000000,0x3f7fdaaf,0xbd0a342f,0x3f7f6ac7,0xbd8a200a,0x3f7eb069,0xbdcefdb7,
0x3f7dabcc,0xbe09cf86,0x3f7c5d3a,0xbe2bf804,0x3f7ac516,0xbe4dee60,0x3f78e3d6,0xbe6fa8b2,0x3f800000,0x80000000,0x3f7fd397,0xbd16c32c,
0x3f7f4e6d,0xbd96a905,0x3f7e70b0,0xbde1bc2e,0x3f7d3aac,0xbe164083,0x3f7baccd,0xbe3b6ecf,0x3f79c79d,0xbe605c13,0x3f778bc5,0xbe827dc0,
0x3f800000,0x80000000,0x3f7fcbe2,0xbd2351cb,0x3f7f2f9d,0xbda3308c,0x3f7e2b72,0xbdf475c0,0x3f7cbfc9,0xbe22abb6,0x3f7aed37,0xbe4ada4f,
0x3f78b47b,0xbe72b651,0x3f76167a,0xbe8d17c0,0x3f800000,0x80000000,0x3f7fc38f,0xbd2fe007,0x3f7f0e58,0xbdafb680,0x3f7de0b1,0xbe039502,
0x3f7c3b28,0xbe2f10a2,0x3f7a1e84,0xbe5a3997,0x3f778bc5,0xbe827dc0,0x3f748422,0xbe97a117,0x3f800000,0x80000000,0x3f7fba9e,0xbd3c6dd5,
0x3f7eea9d,0xbdbc3ac3,0x3f7d906e,0xbe0cec4a,0x3f7baccd,0xbe3b6ecf,0x3f7940c0,0xbe698bba,0x3f764d97,0xbe8b9507,0x3f72d4eb,0xbea21887,
0x3f7b14be,0xbe47c5c2,0x3f79c79d,0xbe605c13,0x3f7853f8,0xbe78cfcc,0x3f76ba07,0xbe888e93,0x3f74fa0b,0xbe94a031,0x3f731447,0xbea09ae5,
0x3f710908,0xbeac7cd4,0x3f6ed89e,0xbeb8442a,0x3f79c79d,0xbe605c13,0x3f7822d1,0xbe7bdba4,0x3f764d97,0xbe8b9507,0x3f74484b,0xbe9920fe,
0x3f721352,0xbea68f12,0x3f6faf1b,0xbeb3dca5,0x3f6d1c1d,0xbec1071e,0x3f6a5ad9,0xbece0bea,0x3f7853f8,0xbe78cfcc,0x3f764d97,0xbe8b9507,
0x3f740bdd,0xbe9aa086,0x3f718f57,0xbea986c4,0x3f6ed89e,0xbeb8442a,0x3f6be858,0xbec6d529,0x3f68bf3c,0xbed53641,0x3f655e0b,0xbee363fa,
0x3f76ba07,0xbe888e93,0x3f74484b,0xbe9920fe,0x3f718f57,0xbea986c4,0x3f6e8ff8,0xbeb9bb1e,0x3f6b4b0c,0xbec9b953,0x3f67c187,0xbed97cb9,
0x3f63f473,0xbee900b7,0x3f5fe4e9,0xbef840c8,0x3f74fa0b,0xbe94a031,0x3f721352,0xbea68f12,0x3f6ed89e,0xbeb8442a,0x3f6b4b0c,0xbec9b953,
0x3f676bd8,0xbedae880,0x3f633c5a,0xbeebcbbb,0x3f5ebe05,0xbefc5d27,0x3f59f26a,0xbf064b82,0x3f731447,0xbea09ae5,0x3f6faf1b,0xbeb3dca5,
0x3f6be858,0xbec6d529,0x3f67c187,0xbed97cb9,0x3f633c5a,0xbeebcbbb,0x3f5e5aa6,0xbefdbabb,0x3f591e6a,0xbf07a136,0x3f5389c7,0xbf102dd5,
0x3f710908,0xbeac7cd4,0x3f6d1c1d,0xbec1071e,0x3f68bf3c,0xbed53641,0x3f63f473,0xbee900b7,0x3f5ebe05,0xbefc5d27,0x3f591e6a,0xbf07a136,
0x3f531849,0xbf10d3cd,0x3f4cae79,0xbf19c200,0x3f6ed89e,0xbeb8442a,0x3f6a5ad9,0xbece0bea,0x3f655e0b,0xbee363fa,0x3f5fe4e9,0xbef840c8,
0x3f59f26a,0xbf064b82,0x3f5389c7,0xbf102dd5,0x3f4cae79,0xbf19c200,0x3f456439,0xbf2302d3,0x3f6c835e,0xbec3ef15,0x3f6a09a7,0xbecf7bca,
0x3f676bd8,0xbedae880,0x3f64aa59,0xbee63375,0x3f61c598,0xbef15aea,0x3f5ebe05,0xbefc5d27,0x3f5b941a,0xbf039c3d,0x3f584853,0xbf08f59b,
0x3f676bd8,0xbedae880,0x3f644fac,0xbee79a5d,0x3f6106f2,0xbef41f07,0x3f5d924d,0xbf003a06,0x3f59f26a,0xbf064b82,0x3f5627fe,0xbf0c42c9,
0x3f5233c6,0xbf121eb0,0x3f4e1689,0xbf17de12,0x3f61c598,0xbef15aea,0x3f5df6be,0xbeff17b2,0x3f59f26a,0xbf064b82,0x3f55b993,0xbf0cead0,
0x3f514d3d,0xbf13682a,0x3f4cae79,0xbf19c200,0x3f47de65,0xbf1ff6cb,0x3f42de29,0xbf26050a,0x3f5b941a,0xbf039c3d,0x3f570348,0xbf0af1b7,
0x3f5233c6,0xbf121eb0,0x3f4d26fd,0xbf19210f,0x3f47de65,0xbf1ff6cb,0x3f425b89,0xbf269de3,0x3f3ca003,0xbf2d1469,0x3f36ad7f,0xbf33587a,
0x3f54db31,0xbf0e39da,0x3f4f7a1f,0xbf15f6d9,0x3f49d112,0xbf1d7fd1,0x3f43e200,0xbf24d225,0x3f3daef9,0xbf2beb4a,0x3f373a23,0xbf32c8c9,
0x3f3085bb,0xbf396842,0x3f299415,0xbf3fc767,0x3f4d9f02,0xbf187fc0,0x3f476085,0xbf209393,0x3f40d0da,0xbf286605,0x3f39f2ac,0xbf2ff3e6,
0x3f32c8c9,0xbf373a23,0x3f2b561b,0xbf3e35c5,0x3f239da9,0xbf44e3f5,0x3f1ba299,0xbf4b41fa,0x3f45e403,0xbf226799,0x3f3ebc1b,0xbf2ac082,
0x3f373a23,0xbf32c8c9,0x3f2f61a5,0xbf3a7ca4,0x3f273656,0xbf41d870,0x3f1ebc12,0xbf48d8b3,0x3f15f6d9,0xbf4f7a1f,0x3f0cead0,0xbf55b993,
0x3f3daef9,0xbf2beb4a,0x3f3592e7,0xbf34768f,0x3f2d1469,0xbf3ca003,0x3f24381a,0xbf446337,0x3f1b02c6,0xbf4bbbf8,0x3f11796b,0xbf52a649,
0x3f07a136,0xbf591e6a,0x3efafef7,0xbf5f20db,0x3f54db31,0xbf0e39da,0x3f514d3d,0xbf13682a,0x3f4d9f02,0xbf187fc0,0x3f49d112,0xbf1d7fd1,
0x3f45e403,0xbf226799,0x3f41d870,0xbf273656,0x3f3daef9,0xbf2beb4a,0x3f396842,0xbf3085bb,0x3f49d112,0xbf1d7fd1,0x3f456439,0xbf2302d3,
0x3f40d0da,0xbf286605,0x3f3c17d9,0xbf2da859,0x3f373a23,0xbf32c8c9,0x3f3238aa,0xbf37c655,0x3f2d1469,0xbf3ca003,0x3f27ce61,0xbf4154e1,
0x3f3daef9,0xbf2beb4a,0x3f385216,0xbf31a81d,0x3f32c8c9,0xbf373a23,0x3f2d1469,0xbf3ca003,0x3f273656,0xbf41d870,0x3f212ff9,0xbf46e22a,
0x3f1b02c6,0xbf4bbbf8,0x3f14b039,0xbf5064af,0x3f3085bb,0xbf396842,0x3f2a2a80,0xbf3f41fc,0x3f239da9,0xbf44e3f5,0x3f1ce11f,0xbf4a4c87,
0x3f15f6d9,0xbf4f7a1f,0x3f0ee0db,0xbf546b3b,0x3f07a136,0xbf591e6a,0x3f003a06,0xbf5d924d,0x3f226799,0xbf45e403,0x3f1b02c6,0xbf4bbbf8,
0x3f13682a,0xbf514d3d,0x3f0b9a6b,0xbf5695e5,0x3f039c3d,0xbf5b941a,0x3ef6e0cb,0xbf604621,0x3ee63375,0xbf64aa59,0x3ed53641,0xbf68bf3c,
0x3f13682a,0xbf514d3d,0x3f0af1b7,0xbf570348,0x3f0242b1,0xbf5c61c7,0x3ef2bd43,0xbf61668a,0x3ee0924f,0xbf660f88,0x3ece0bea,0xbf6a5ad9,
0x3ebb31a0,0xbf6e46be,0x3ea80b1f,0xbf71d19f,0x3f039c3d,0xbf5b941a,0x3ef41f07,0xbf6106f2,0x3ee0924f,0xbf660f88,0x3ecc9b8b,0xbf6aab7b,
0x3eb8442a,0xbf6ed89e,0x3ea395c5,0xbf7294f8,0x3e8e9a22,0xbf75dec6,0x3e72b651,0xbf78b47b,0x3ee63375,0xbf64aa59,0x3ed0eb2a,0xbf69b7e4,
0x3ebb31a0,0xbf6e46be,0x3ea5129f,0xbf725470,0x3e8e9a22,0xbf75dec6,0x3e6fa8b2,0xbf78e3d6,0x3e419b37,0xbf7b61fc,0x3e1324ca,0xbf7d57de,
0x3f3504f3,0xbf3504f3,0x3f3085bb,0xbf396842,0x3f2beb4a,0xbf3daef9,0x3f273656,0xbf41d870,0x3f226799,0xbf45e403,0x3f1d7fd1,0xbf49d112,
0x3f187fc0,0xbf4d9f02,0x3f13682a,0xbf514d3d,0x3f226799,0xbf45e403,0x3f1ce11f,0xbf4a4c87,0x3f173c07,0xbf4e8d90,0x3f11796b,0xbf52a649,
0x3f0b9a6b,0xbf5695e5,0x3f05a02c,0xbf5a5ba0,0x3eff17b2,0xbf5df6be,0x3ef2bd43,0xbf61668a,0x3f0e39da,0xbf54db31,0x3f07a136,0xbf591e6a,
0x3f00e7e4,0xbf5d2d53,0x3ef41f07,0xbf6106f2,0x3ee63375,0xbf64aa59,0x3ed8106b,0xbf6816a8,0x3ec9b953,0xbf6b4b0c,0x3ebb31a0,0xbf6e46be,
0x3ef15aea,0xbf61c598,0x3ee1fb6a,0xbf65b710,0x3ed25a09,0xbf696591,0x3ec27b55,0xbf6cd007,0x3eb263ef,0xbf6ff573,0x3ea21887,0xbf72d4eb,
0x3e919ddd,0xbf756d97,0x3e80f8c0,0xbf77beb7,0x3ec3ef15,0xbf6c835e,0x3eb263ef,0xbf6ff573,0x3ea09ae5,0xbf731447,0x3e8e9a22,0xbf75dec6,
0x3e78cfcc,0xbf7853f8,0x3e541501,0xbf7a7302,0x3e2f10a2,0xbf7c3b28,0x3e09cf86,0xbf7dabcc,0x3e94a031,0xbf74fa0b,0x3e80f8c0,0xbf77beb7,
0x3e5a3997,0xbf7a1e84,0x3e3228d4,0xbf7c187a,0x3e09cf86,0xbf7dabcc,0x3dc27c39,0xbf7ed7d4,0x3d621469,0xbf7f9c18,0x3c7b514b,0xbf7ff84a,
0x3e47c5c2,0xbf7b14be,0x3e1c76de,0xbf7cfe73,0x3de1bc2e,0xbf7e70b0,0x3d8a200a,0xbf7f6ac7,0x3cc90ab0,0xbf7fec43,0xbc96c9b6,0xbf7ff4e6,
0xbd7b2b74,0xbf7f84ab,0xbdd53db9,0xbf7e9bc9,0x3dc8bd36,0xbf7ec46d,0x3d55880e,0xbf7fa6e3,0x3bc90f88,0xbf7ffec4,0xbd2351cb,0xbf7fcbe2,
0xbdafb680,0xbf7f0e58,0xbe06b26e,0xbf7dc68c,0xbe354098,0xbf7bf531,0xbe636c83,0xbf799b43,0x3f0e39da,0xbf54db31,0x3f08f59b,0xbf584853,
0x3f039c3d,0xbf5b941a,0x3efc5d27,0xbf5ebe05,0x3ef15aea,0xbf61c598,0x3ee63375,0xbf64aa59,0x3edae880,0xbf676bd8,0x3ecf7bca,0xbf6a09a7,
0x3ee63375,0xbf64aa59,0x3ed97cb9,0xbf67c187,0x3ecc9b8b,0xbf6aab7b,0x3ebf926f,0xbf6d67a1,0x3eb263ef,0xbf6ff573,0x3ea5129f,0xbf725470,
0x3e97a117,0xbf748422,0x3e8a11f7,0xbf76841b,0x3eac7cd4,0xbf710908,0x3e9d9e78,0xbf73913f,0x3e8e9a22,0xbf75dec6,0x3e7ee6e1,0xbf77f110,
0x3e605c13,0xbf79c79d,0x3e419b37,0xbf7b61fc,0x3e22abb6,0xbf7cbfc9,0x3e039502,0xbf7de0b1,0x3e605c13,0xbf79c79d,0x3e3e853e,0xbf7b87b2,
0x3e1c76de,0xbf7cfe73,0x3df475c0,0xbf7e2b72,0x3dafb680,0xbf7f0e58,0x3d55880e,0xbf7fa6e3,0x3c96c9b6,0xbf7ff4e6,0xbc7b514b,0xbf7ff84a,
0x3dc8bd36,0xbf7ec46d,0x3d7b2b74,0xbf7f84ab,0x3cc90ab0,0xbf7fec43,0xbc490e90,0xbf7ffb11,0xbd48fb30,0xbf7fb10f,0xbdafb680,0xbf7f0e58,
0xbdfab273,0xbf7e1324,0xbe22abb6,0xbf7cbfc9,0xbcc90ab0,0xbf7fec43,0xbd83db0a,0xbf7f7808,0xbdd53db9,0xbf7e9bc9,0xbe1324ca,0xbf7d57de,
0xbe3b6ecf,0xbf7baccd,0xbe636c83,0xbf799b43,0xbe8586ce,0xbf772417,0xbe9920fe,0xbf74484b,0xbe164083,0xbf7d3aac,0xbe419b37,0xbf7b61fc,
0xbe6c9a7f,0xbf791298,0xbe8b9507,0xbf764d97,0xbea09ae5,0xbf731447,0xbeb554ec,0xbf6f6830,0xbec9b953,0xbf6b4b0c,0xbeddbe79,0xbf66becc,
0xbe888e93,0xbf76ba07,0xbe9f1cdf,0xbf73530e,0xbeb554ec,0xbf6f6830,0xbecb2aae,0xbf6afb8c,0xbee0924f,0xbf660f88,0xbef58035,0xbf60a6cf,
0xbf04f484,0xbf5ac450,0xbf0ee0db,0xbf546b3b,0x3ec3ef15,0xbf6c835e,0x3eb8442a,0xbf6ed89e,0x3eac7cd4,0xbf710908,0x3ea09ae5,0xbf731447,
0x3e94a031,0xbf74fa0b,0x3e888e93,0xbf76ba07,0x3e78cfcc,0xbf7853f8,0x3e605c13,0xbf79c79d,0x3e78cfcc,0xbf7853f8,0x3e5d4b1a,0xbf79f35e,
0x3e419b37,0xbf7b61fc,0x3e25c58c,0xbf7c9f8a,0x3e09cf86,0xbf7dabcc,0x3ddb7d37,0xbf7e868b,0x3da3308c,0xbf7f2f9d,0x3d55880e,0xbf7fa6e3,
0x3dc8bd36,0xbf7ec46d,0x3d8a200a,0xbf7f6ac7,0x3d16c32c,0xbf7fd397,0x3bc90f88,0xbf7ffec4,0xbcc90ab0,0xbf7fec43,0xbd621469,0xbf7f9c18,
0xbdafb680,0xbf7f0e58,0xbdee3876,0xbf7e4323,0xbd48fb30,0xbf7fb10f,0xbda973ba,0xbf7f1f49,0xbdee3876,0xbf7e4323,0xbe195be0,0xbf7d1cdd,
0xbe3b6ecf,0xbf7baccd,0xbe5d4b1a,0xbf79f35e,0xbe7ee6e1,0xbf77f110,0xbe901c2c,0xbf75a67b,0xbe47c5c2,0xbf7b14be,0xbe6c9a7f,0xbf791298,
0xbe888e93,0xbf76ba07,0xbe9aa086,0xbf740bdd,0xbeac7cd4,0xbf710908,0xbebe1d4a,0xbf6db293,0xbecf7bca,0xbf6a09a7,0xbee0924f,0xbf660f88,
0xbeac7cd4,0xbf710908,0xbebf926f,0xbf6d67a1,0xbed25a09,0xbf696591,0xbee4cbfe,0xbf650479,0xbef6e0cb,0xbf604621,0xbf044889,0xbf5b2c79,
0xbf0cead0,0xbf55b993,0xbf1553b7,0xbf4fefa8,0xbef15aea,0xbf61c598,0xbf0242b1,0xbf5c61c7,0xbf0b9a6b,0xbf5695e5,0xbf14b039,0xbf5064af,
0xbf1d7fd1,0xbf49d112,0xbf26050a,0xbf42de29,0xbf2e3bde,0xbf3b8f3b,0xbf36206c,0xbf33e7bc,0xbf187fc0,0xbf4d9f02,0xbf21cbfb,0xbf466354,
0xbf2ac082,0xbf3ebc1b,0xbf33587a,0xbf36ad7f,0xbf3b8f3b,0xbf2e3bde,0xbf436051,0xbf256bcb,0xbf4ac77f,0xbf1c420c,0xbf51c0c2,0xbf12c39a,
0x3e47c5c2,0xbf7b14be,0x3e2f10a2,0xbf7c3b28,0x3e164083,0xbf7d3aac,0x3dfab273,0xbf7e1324,0x3dc8bd36,0xbf7ec46d,0x3d96a905,0xbf7f4e6d,
0x3d48fb30,0xbf7fb10f,0x3cc90ab0,0xbf7fec43,0x3cc90ab0,0xbf7fec43,0xbb490fc6,0xbf7fffb1,0xbcfb49ba,0xbf7fe129,0xbd6ea038,0xbf7f90b1,
0xbdafb680,0xbf7f0e58,0xbde7fa9a,0xbf7e5a38,0xbe1008b7,0xbf7d7474,0xbe2bf804,0xbf7c5d3a,0xbe164083,0xbf7d3aac,0xbe354098,0xbf7bf531,
0xbe541501,0xbf7a7302,0xbe72b651,0xbf78b47b,0xbe888e93,0xbf76ba07,0xbe97a117,0xbf748422,0xbea68f12,0xbf721352,0xbeb554ec,0xbf6f6830,
0xbea09ae5,0xbf731447,0xbeb0eacb,0xbf703b37,0xbec1071e,0xbf6d1c1d,0xbed0eb2a,0xbf69b7e4,0xbee0924f,0xbf660f88,0xbeeff7fb,0xbf62241a,
0xbeff17b2,0xbf5df6be,0xbf06f686,0xbf5988ad,0xbef15aea,0xbf61c598,0xbf00e7e4,0xbf5d2d53,0xbf08f59b,0xbf584853,0xbf10d3cd,0xbf531849,
0xbf187fc0,0xbf4d9f02,0xbf1ff6cb,0xbf47de65,0xbf273656,0xbf41d870,0xbf2e3bde,0xbf3b8f3b,0xbf1d7fd1,0xbf49d112,0xbf256bcb,0xbf436051,
0xbf2d1469,0xbf3ca003,0xbf34768f,0xbf3592e7,0xbf3b8f3b,0xbf2e3bde,0xbf425b89,0xbf269de3,0xbf48d8b3,0xbf1ebc12,0xbf4f0417,0xbf16999f,
0xbf3daef9,0xbf2beb4a,0xbf44e3f5,0xbf239da9,0xbf4bbbf8,0xbf1b02c6,0xbf5233c6,0xbf121eb0,0xbf584853,0xbf08f59b,0xbf5df6be,0xbeff17b2,
0xbf633c5a,0xbeebcbbb,0xbf6816a8,0xbed8106b,0xbf584853,0xbf08f59b,0xbf5e5aa6,0xbefdbabb,0xbf63f473,0xbee900b7,0xbf6912ae,0xbed3c867,
0xbf6db293,0xbebe1d4a,0xbf71d19f,0xbea80b1f,0xbf756d97,0xbe919ddd,0xbf788486,0xbe75c35a,0x3f800000,0x80000000,0x3f7fb10f,0xbd48fb30,
0x3f7ec46d,0xbdc8bd36,0x3f7d3aac,0xbe164083,0x3f7b14be,0xbe47c5c2,0x3f7853f8,0xbe78cfcc,0x3f74fa0b,0xbe94a031,0x3f710908,0xbeac7cd4,
0x3f800000,0x80000000,0x3f7fa6e3,0xbd55880e,0x3f7e9bc9,0xbdd53db9,0x3f7cdf6c,0xbe1f917b,0x3f7a7302,0xbe541501,0x3f77583a,0xbe840270,
0x3f73913f,0xbe9d9e78,0x3f6f20b0,0xbeb6ccc3,0x3f800000,0x80000000,0x3f7f9c18,0xbd621469,0x3f7e70b0,0xbde1bc2e,0x3f7c7eb0,0xbe28defc,
0x3f79c79d,0xbe605c13,0x3f764d97,0xbe8b9507,0x3f721352,0xbea68f12,0x3f6d1c1d,0xbec1071e,0x3f800000,0x80000000,0x3f7f90b1,0xbd6ea038,
0x3f7e4323,0xbdee3876,0x3f7c187a,0xbe3228d4,0x3f791298,0xbe6c9a7f,0x3f75341d,0xbe931f35,0x3f708066,0xbeaf713a,0x3f6afb8c,0xbecb2aae,
0x3f800000,0x80000000,0x3f7f84ab,0xbd7b2b74,0x3f7e1324,0xbdfab273,0x3f7baccd,0xbe3b6ecf,0x3f7853f8,0xbe78cfcc,0x3f740bdd,0xbe9aa086,
0x3f6ed89e,0xbeb8442a,0x3f68bf3c,0xbed53641,0x3f800000,0x80000000,0x3f7f7808,0xbd83db0a,0x3f7de0b1,0xbe039502,0x3f7b3bab,0xbe44b0b9,
0x3f778bc5,0xbe827dc0,0x3f72d4eb,0xbea21887,0x3f6d1c1d,0xbec1071e,0x3f666771,0xbedf28a9,0x3f800000,0x80000000,0x3f7f6ac7,0xbd8a200a,
0x3f7dabcc,0xbe09cf86,0x3f7ac516,0xbe4dee60,0x3f76ba07,0xbe888e93,0x3f718f57,0xbea986c4,0x3f6b4b0c,0xbec9b953,0x3f63f473,0xbee900b7,
0x3f800000,0x80000000,0x3f7f5ce9,0xbd9064b4,0x3f7d7474,0xbe1008b7,0x3f7a4910,0xbe57278f,0x3f75dec6,0xbe8e9a22,0x3f703b37,0xbeb0eacb,
0x3f696591,0xbed25a09,0x3f61668a,0xbef2bd43,0x3f6c835e,0xbec3ef15,0x3f676bd8,0xbedae880,0x3f61c598,0xbef15aea,0x3f5b941a,0xbf039c3d,
0x3f54db31,0xbf0e39da,0x3f4d9f02,0xbf187fc0,0x3f45e403,0xbf226799,0x3f3daef9,0xbf2beb4a,0x3f6a09a7,0xbecf7bca,0x3f644fac,0xbee79a5d,
0x3f5df6be,0xbeff17b2,0x3f570348,0xbf0af1b7,0x3f4f7a1f,0xbf15f6d9,0x3f476085,0xbf209393,0x3f3ebc1b,0xbf2ac082,0x3f3592e7,0xbf34768f,
0x3f676bd8,0xbedae880,0x3f6106f2,0xbef41f07,0x3f59f26a,0xbf064b82,0x3f5233c6,0xbf121eb0,0x3f49d112,0xbf1d7fd1,0x3f40d0da,0xbf286605,
0x3f373a23,0xbf32c8c9,0x3f2d1469,0xbf3ca003,0x3f64aa59,0xbee63375,0x3f5d924d,0xbf003a06,0x3f55b993,0xbf0cead0,0x3f4d26fd,0xbf19210f,
0x3f43e200,0xbf24d225,0x3f39f2ac,0xbf2ff3e6,0x3f2f61a5,0xbf3a7ca4,0x3f24381a,0xbf446337,0x3f61c598,0xbef15aea,0x3f59f26a,0xbf064b82,
0x3f514d3d,0xbf13682a,0x3f47de65,0xbf1ff6cb,0x3f3daef9,0xbf2beb4a,0x3f32c8c9,0xbf373a23,0x3f273656,0xbf41d870,0x3f1b02c6,0xbf4bbbf8,
0x3f5ebe05,0xbefc5d27,0x3f5627fe,0xbf0c42c9,0x3f4cae79,0xbf19c200,0x3f425b89,0xbf269de3,0x3f373a23,0xbf32c8c9,0x3f2b561b,0xbf3e35c5,
0x3f1ebc12,0xbf48d8b3,0x3f11796b,0xbf52a649,0x3f5b941a,0xbf039c3d,0x3f5233c6,0xbf121eb0,0x3f47de65,0xbf1ff6cb,0x3f3ca003,0xbf2d1469,
0x3f3085bb,0xbf396842,0x3f239da9,0xbf44e3f5,0x3f15f6d9,0xbf4f7a1f,0x3f07a136,0xbf591e6a,0x3f584853,0xbf08f59b,0x3f4e1689,0xbf17de12,
0x3f42de29,0xbf26050a,0x3f36ad7f,0xbf33587a,0x3f299415,0xbf3fc767,0x3f1ba299,0xbf4b41fa,0x3f0cead0,0xbf55b993,0x3efafef7,0xbf5f20db,
0x3f3504f3,0xbf3504f3,0x3f2beb4a,0xbf3daef9,0x3f226799,0xbf45e403,0x3f187fc0,0xbf4d9f02,0x3f0e39da,0xbf54db31,0x3f039c3d,0xbf5b941a,
0x3ef15aea,0xbf61c598,0x3edae880,0xbf676bd8,0x3f2beb4a,0xbf3daef9,0x3f21cbfb,0xbf466354,0x3f173c07,0xbf4e8d90,0x3f0c42c9,0xbf5627fe,
0x3f00e7e4,0xbf5d2d53,0x3eea6681,0xbf6398ac,0x3ed25a09,0xbf696591,0x3eb9bb1e,0xbf6e8ff8,0x3f226799,0xbf45e403,0x3f173c07,0xbf4e8d90,
0x3f0b9a6b,0xbf5695e5,0x3eff17b2,0xbf5df6be,0x3ee63375,0xbf64aa59,0x3ecc9b8b,0xbf6aab7b,0x3eb263ef,0xbf6ff573,0x3e97a117,0xbf748422,
0x3f187fc0,0xbf4d9f02,0x3f0c42c9,0xbf5627fe,0x3eff17b2,0xbf5df6be,0x3ee4cbfe,0xbf650479,0x3ec9b953,0xbf6b4b0c,0x3eadf73c,0xbf70c501,
0x3e919ddd,0xbf756d97,0x3e698bba,0xbf7940c0,0x3f0e39da,0xbf54db31,0x3f00e7e4,0xbf5d2d53,0x3ee63375,0xbf64aa59,0x3ec9b953,0xbf6b4b0c,
0x3eac7cd4,0xbf710908,0x3e8e9a22,0xbf75dec6,0x3e605c13,0xbf79c79d,0x3e22abb6,0xbf7cbfc9,0x3f039c3d,0xbf5b941a,0x3eea6681,0xbf6398ac,
0x3ecc9b8b,0xbf6aab7b,0x3eadf73c,0xbf70c501,0x3e8e9a22,0xbf75dec6,0x3e5d4b1a,0xbf79f35e,0x3e1c76de,0xbf7cfe73,0x3db5f8da,0xbf7efcc9,
0x3ef15aea,0xbf61c598,0x3ed25a09,0xbf696591,0x3eb263ef,0xbf6ff573,0x3e919ddd,0xbf756d97,0x3e605c13,0xbf79c79d,0x3e1c76de,0xbf7cfe73,
0x3dafb680,0xbf7f0e58,0x3c96c9b6,0xbf7ff4e6,0x3edae880,0xbf676bd8,0x3eb9bb1e,0xbf6e8ff8,0x3e97a117,0xbf748422,0x3e698bba,0xbf7940c0,
0x3e22abb6,0xbf7cbfc9,0x3db5f8da,0xbf7efcc9,0x3c96c9b6,0xbf7ff4e6,0xbd55880e,0xbf7fa6e3,0x3ec3ef15,0xbf6c835e,0x3eac7cd4,0xbf710908,
0x3e94a031,0xbf74fa0b,0x3e78cfcc,0xbf7853f8,0x3e47c5c2,0xbf7b14be,0x3e164083,0xbf7d3aac,0x3dc8bd36,0xbf7ec46d,0x3d48fb30,0xbf7fb10f,
0x3ea09ae5,0xbf731447,0x3e870ada,0xbf76ef5b,0x3e5a3997,0xbf7a1e84,0x3e25c58c,0xbf7c9f8a,0x3de1bc2e,0xbf7e70b0,0x3d6ea038,0xbf7f90b1,
0x3bc90f88,0xbf7ffec4,0xbd3c6dd5,0xbf7fba9e,0x3e78cfcc,0xbf7853f8,0x3e419b37,0xbf7b61fc,0x3e09cf86,0xbf7dabcc,0x3da3308c,0xbf7f2f9d,
0x3cc90ab0,0xbf7fec43,0xbcfb49ba,0xbf7fe129,0xbdafb680,0xbf7f0e58,0xbe1008b7,0xbf7d7474,0x3e2f10a2,0xbf7c3b28,0x3de7fa9a,0xbf7e5a38,
0x3d621469,0xbf7f9c18,0xbb490fc6,0xbf7fffb1,0xbd7b2b74,0xbf7f84ab,0xbdf475c0,0xbf7e2b72,0xbe354098,0xbf7bf531,0xbe6fa8b2,0xbf78e3d6,
0x3dc8bd36,0xbf7ec46d,0x3d16c32c,0xbf7fd397,0xbcc90ab0,0xbf7fec43,0xbdafb680,0xbf7f0e58,0xbe164083,0xbf7d3aac,0xbe541501,0xbf7a7302,
0xbe888e93,0xbf76ba07,0xbea68f12,0xbf721352,0x3cc90ab0,0xbf7fec43,0xbd2351cb,0xbf7fcbe2,0xbdd53db9,0xbf7e9bc9,0xbe2bf804,0xbf7c5d3a,
0xbe6c9a7f,0xbf791298,0xbe9620d2,0xbf74bf62,0xbeb554ec,0xbf6f6830,0xbed3c867,0xbf6912ae,0xbd48fb30,0xbf7fb10f,0xbdee3876,0xbf7e4323,
0xbe3b6ecf,0xbf7baccd,0xbe7ee6e1,0xbf77f110,0xbea09ae5,0xbf731447,0xbec1071e,0xbf6d1c1d,0xbee0924f,0xbf660f88,0xbeff17b2,0xbf5df6be,
0xbdfab273,0xbf7e1324,0xbe44b0b9,0xbf7b3bab,0xbe8586ce,0xbf772417,0xbea80b1f,0xbf71d19f,0xbec9b953,0xbf6b4b0c,0xbeea6681,0xbf6398ac,
0xbf04f484,0xbf5ac450,0xbf140c5f,0xbf50d937,0x248d3132,0xbf800000,0xbd48fb30,0xbf7fb10f,0xbdc8bd36,0xbf7ec46d,0xbe164083,0xbf7d3aac,
0xbe47c5c2,0xbf7b14be,0xbe78cfcc,0xbf7853f8,0xbe94a031,0xbf74fa0b,0xbeac7cd4,0xbf710908,0xbdc8bd36,0xbf7ec46d,0xbe195be0,0xbf7d1cdd,
0xbe4dee60,0xbf7ac516,0xbe80f8c0,0xbf77beb7,0xbe9aa086,0xbf740bdd,0xbeb3dca5,0xbf6faf1b,0xbecc9b8b,0xbf6aab7b,0xbee4cbfe,0xbf650479,
0xbe47c5c2,0xbf7b14be,0xbe7ee6e1,0xbf77f110,0xbe9aa086,0xbf740bdd,0xbeb554ec,0xbf6f6830,0xbecf7bca,0xbf6a09a7,0xbee900b7,0xbf63f473,
0xbf00e7e4,0xbf5d2d53,0xbf0cead0,0xbf55b993,0xbe94a031,0xbf74fa0b,0xbeb0eacb,0xbf703b37,0xbecc9b8b,0xbf6aab7b,0xbee79a5d,0xbf644fac,
0xbf00e7e4,0xbf5d2d53,0xbf0d9281,0xbf554aa4,0xbf19c200,0xbf4cae79,0xbf256bcb,0xbf436051,0xbec3ef15,0xbf6c835e,0xbee0924f,0xbf660f88,
0xbefc5d27,0xbf5ebe05,0xbf0b9a6b,0xbf5695e5,0xbf187fc0,0xbf4d9f02,0xbf24d225,0xbf43e200,0xbf3085bb,0xbf396842,0xbf3b8f3b,0xbf2e3bde,
0xbef15aea,0xbf61c598,0xbf06f686,0xbf5988ad,0xbf14b039,0xbf5064af,0xbf21cbfb,0xbf466354,0xbf2e3bde,0xbf3b8f3b,0xbf39f2ac,0xbf2ff3e6,
0xbf44e3f5,0xbf239da9,0xbf4f0417,0xbf16999f,0xbf0e39da,0xbf54db31,0xbf1c420c,0xbf4ac77f,0xbf299415,0xbf3fc767,0xbf36206c,0xbf33e7bc,
0xbf41d870,0xbf273656,0xbf4cae79,0xbf19c200,0xbf5695e5,0xbf0b9a6b,0xbf5f8327,0xbef9a02d,0xbf226799,0xbf45e403,0xbf2ff3e6,0xbf39f2ac,
0xbf3ca003,0xbf2d1469,0xbf485bca,0xbf1f599f,0xbf531849,0xbf10d3cd,0xbf5cc7d1,0xbf019573,0xbf655e0b,0xbee363fa,0xbf6cd007,0xbec27b55,
0xbec3ef15,0xbf6c835e,0xbedae880,0xbf676bd8,0xbef15aea,0xbf61c598,0xbf039c3d,0xbf5b941a,0xbf0e39da,0xbf54db31,0xbf187fc0,0xbf4d9f02,
0xbf226799,0xbf45e403,0xbf2beb4a,0xbf3daef9,0xbefc5d27,0xbf5ebe05,0xbf099f4e,0xbf57dc7f,0xbf14b039,0xbf5064af,0xbf1f599f,0xbf485bca,
0xbf299415,0xbf3fc767,0xbf33587a,0xbf36ad7f,0xbf3ca003,0xbf2d1469,0xbf456439,0xbf2302d3,0xbf187fc0,0xbf4d9f02,0xbf239da9,0xbf44e3f5,
0xbf2e3bde,0xbf3b8f3b,0xbf385216,0xbf31a81d,0xbf41d870,0xbf273656,0xbf4ac77f,0xbf1c420c,0xbf531849,0xbf10d3cd,0xbf5ac450,0xbf04f484,
0xbf3085bb,0xbf396842,0xbf3b0629,0xbf2ecef7,0xbf44e3f5,0xbf239da9,0xbf4e1689,0xbf17de12,0xbf5695e5,0xbf0b9a6b,0xbf5e5aa6,0xbefdbabb,
0xbf655e0b,0xbee363fa,0xbf6b99fb,0xbec8477c,0xbf45e403,0xbf226799,0xbf4f7a1f,0xbf15f6d9,0xbf584853,0xbf08f59b,0xbf604621,0xbef6e0cb,
0xbf676bd8,0xbedae880,0xbf6db293,0xbebe1d4a,0xbf731447,0xbea09ae5,0xbf778bc5,0xbe827dc0,0xbf584853,0xbf08f59b,0xbf60a6cf,0xbef58035,
0xbf6816a8,0xbed8106b,0xbf6e8ff8,0xbeb9bb1e,0xbf740bdd,0xbe9aa086,0xbf788486,0xbe75c35a,0xbf7bf531,0xbe354098,0xbf7e5a38,0xbde7fa9a,
0xbf676bd8,0xbedae880,0xbf6e46be,0xbebb31a0,0xbf740bdd,0xbe9aa086,0xbf78b47b,0xbe72b651,0xbf7c3b28,0xbe2f10a2,0xbf7e9bc9,0xbdd53db9,
0xbf7fd397,0xbd16c32c,0xbf7fe129,0x3cfb49ba,0xbf731447,0xbea09ae5,0xbf7822d1,0xbe7bdba4,0xbf7bf531,0xbe354098,0xbf7e868b,0xbddb7d37,
0xbf7fd397,0xbd16c32c,0xbf7fdaaf,0x3d0a342f,0xbf7e9bc9,0x3dd53db9,0xbf7c187a,0x3e3228d4,0xbf3504f3,0xbf3504f3,0xbf3daef9,0xbf2beb4a,
0xbf45e403,0xbf226799,0xbf4d9f02,0xbf187fc0,0xbf54db31,0xbf0e39da,0xbf5b941a,0xbf039c3d,0xbf61c598,0xbef15aea,0xbf676bd8,0xbedae880,
0xbf4d9f02,0xbf187fc0,0xbf554aa4,0xbf0d9281,0xbf5c61c7,0xbf0242b1,0xbf62df7b,0xbeed3063,0xbf68bf3c,0xbed53641,0xbf6dfcf2,0xbebca7af,
0xbf7294f8,0xbea395c5,0xbf76841b,0xbe8a11f7,0xbf61c598,0xbef15aea,0xbf6816a8,0xbed8106b,0xbf6db293,0xbebe1d4a,0xbf7294f8,0xbea395c5,
0xbf76ba07,0xbe888e93,0xbf7a1e84,0xbe5a3997,0xbf7cbfc9,0xbe22abb6,0xbf7e9bc9,0xbdd53db9,0xbf710908,0xbeac7cd4,0xbf75a67b,0xbe901c2c,
0xbf796e4e,0xbe667c66,0xbf7c5d3a,0xbe2bf804,0xbf7e70b0,0xbde1bc2e,0xbf7fa6e3,0xbd55880e,0xbf7ffec4,0x3bc90f88,0xbf7f7808,0x3d83db0a,
0xbf7b14be,0xbe47c5c2,0xbf7dabcc,0xbe09cf86,0xbf7f4e6d,0xbd96a905,0xbf7ffb11,0xbc490e90,0xbf7fb10f,0x3d48fb30,0xbf7e70b0,0x3de1bc2e,
0xbf7c3b28,0x3e2f10a2,0xbf791298,0x3e6c9a7f,0xbf7fb10f,0xbd48fb30,0xbf7ff84a,0x3c7b514b,0xbf7f2f9d,0x3da3308c,0xbf7d57de,0x3e1324ca,
0xbf7a7302,0x3e541501,0xbf76841b,0x3e8a11f7,0xbf718f57,0x3ea986c4,0xbf6b99fb,0x3ec8477c,0xbf7ec46d,0x3dc8bd36,0xbf7c7eb0,0x3e28defc,
0xbf791298,0x3e6c9a7f,0xbf748422,0x3e97a117,0xbf6ed89e,0x3eb8442a,0xbf6816a8,0x3ed8106b,0xbf604621,0x3ef6e0cb,0xbf577026,0x3f0a48ad,
0xbf7853f8,0x3e78cfcc,0xbf73530e,0x3e9f1cdf,0xbf6d1c1d,0x3ec1071e,0xbf65b710,0x3ee1fb6a,0xbf5d2d53,0x3f00e7e4,0xbf5389c7,0x3f102dd5,
0xbf48d8b3,0x3f1ebc12,0xbf3d27b8,0x3f2c800f,0xbf6c835e,0xbec3ef15,0xbf710908,0xbeac7cd4,0xbf74fa0b,0xbe94a031,0xbf7853f8,0xbe78cfcc,
0xbf7b14be,0xbe47c5c2,0xbf7d3aac,0xbe164083,0xbf7ec46d,0xbdc8bd36,0xbf7fb10f,0xbd48fb30,0xbf79c79d,0xbe605c13,0xbf7c5d3a,0xbe2bf804,
0xbf7e4323,0xbdee3876,0xbf7f7808,0xbd83db0a,0xbf7ffb11,0xbc490e90,0xbf7fcbe2,0x3d2351cb,0xbf7eea9d,0x3dbc3ac3,0xbf7d57de,0x3e1324ca,
0xbf7fb10f,0xbd48fb30,0xbf7ffec4,0x3bc90f88,0xbf7f84ab,0x3d7b2b74,0xbf7e4323,0x3dee3876,0xbf7c3b28,0x3e2f10a2,0xbf796e4e,0x3e667c66,
0xbf75dec6,0x3e8e9a22,0xbf718f57,0x3ea986c4,0xbf7e1324,0x3dfab273,0xbf7bd14d,0x3e3857ec,0xbf78b47b,0x3e72b651,0xbf74bf62,0x3e9620d2,
0xbf6ff573,0x3eb263ef,0xbf6a5ad9,0x3ece0bea,0xbf63f473,0x3ee900b7,0xbf5cc7d1,0x3f019573,0xbf74fa0b,0x3e94a031,0xbf6ff573,0x3eb263ef,
0xbf6a09a7,0x3ecf7bca,0xbf633c5a,0x3eebcbbb,0xbf5b941a,0x3f039c3d,0xbf531849,0x3f10d3cd,0xbf49d112,0x3f1d7fd1,0xbf3fc767,0x3f299415,
0xbf64aa59,0x3ee63375,0xbf5cc7d1,0x3f019573,0xbf53fac3,0x3f0f8784,0xbf4a4c87,0x3f1ce11f,0xbf3fc767,0x3f299415,0xbf34768f,0x3f3592e7,
0xbf286605,0x3f40d0da,0xbf1ba299,0x3f4b41fa,0xbf4d9f02,0x3f187fc0,0xbf42de29,0x3f26050a,0xbf373a23,0x3f32c8c9,0xbf2ac082,0x3f3ebc1b,
0xbf1d7fd1,0x3f49d112,0xbf0f8784,0x3f53fac3,0xbf00e7e4,0x3f5d2d53,0xbee363fa,0x3f655e0b,0xbf3085bb,0x3f396842,0xbf2302d3,0x3f456439,
0xbf14b039,0x3f5064af,0xbf05a02c,0x3f5a5ba0,0xbeebcbbb,0x3f633c5a,0xbecb2aae,0x3f6afb8c,0xbea986c4,0x3f718f57,0xbe870ada,0x3f76ef5b,
0x3f800000,0x80000000,0x3f7f4e6d,0xbd96a905,0x3f7d3aac,0xbe164083,0x3f79c79d,0xbe605c13,0x3f74fa0b,0xbe94a031,0x3f6ed89e,0xbeb8442a,
0x3f676bd8,0xbedae880,0x3f5ebe05,0xbefc5d27,0x3f800000,0x80000000,0x3f7f3f54,0xbd9cecf9,0x3f7cfe73,0xbe1c76de,0x3f7940c0,0xbe698bba,
0x3f740bdd,0xbe9aa086,0x3f6d67a1,0xbebf926f,0x3f655e0b,0xbee363fa,0x3f5bfb34,0xbf02ef9f,0x3f800000,0x80000000,0x3f7f2f9d,0xbda3308c,
0x3f7cbfc9,0xbe22abb6,0x3f78b47b,0xbe72b651,0x3f731447,0xbea09ae5,0x3f6be858,0xbec6d529,0x3f633c5a,0xbeebcbbb,0x3f591e6a,0xbf07a136,
0x3f800000,0x80000000,0x3f7f1f49,0xbda973ba,0x3f7c7eb0,0xbe28defc,0x3f7822d1,0xbe7bdba4,0x3f721352,0xbea68f12,0x3f6a5ad9,0xbece0bea,
0x3f6106f2,0xbef41f07,0x3f5627fe,0xbf0c42c9,0x3f800000,0x80000000,0x3f7f0e58,0xbdafb680,0x3f7c3b28,0xbe2f10a2,0x3f778bc5,0xbe827dc0,
0x3f710908,0xbeac7cd4,0x3f68bf3c,0xbed53641,0x3f5ebe05,0xbefc5d27,0x3f531849,0xbf10d3cd,0x3f800000,0x80000000,0x3f7efcc9,0xbdb5f8da,
0x3f7bf531,0xbe354098,0x3f76ef5b,0xbe870ada,0x3f6ff573,0xbeb263ef,0x3f671599,0xbedc53c1,0x3f5c61c7,0xbf0242b1,0x3f4fefa8,0xbf1553b7,
0x3f800000,0x80000000,0x3f7eea9d,0xbdbc3ac3,0x3f7baccd,0xbe3b6ecf,0x3f764d97,0xbe8b9507,0x3f6ed89e,0xbeb8442a,0x3f655e0b,0xbee363fa,
0x3f59f26a,0xbf064b82,0x3f4cae79,0xbf19c200,0x3f800000,0x80000000,0x3f7ed7d4,0xbdc27c39,0x3f7b61fc,0xbe419b37,0x3f75a67b,0xbe901c2c,
0x3f6db293,0xbebe1d4a,0x3f6398ac,0xbeea6681,0x3f577026,0xbf0a48ad,0x3f495521,0xbf1e1e22,0x3f54db31,0xbf0e39da,0x3f49d112,0xbf1d7fd1,
0x3f3daef9,0xbf2beb4a,0x3f3085bb,0xbf396842,0x3f226799,0xbf45e403,0x3f13682a,0xbf514d3d,0x3f039c3d,0xbf5b941a,0x3ee63375,0xbf64aa59,
0x3f514d3d,0xbf13682a,0x3f456439,0xbf2302d3,0x3f385216,0xbf31a81d,0x3f2a2a80,0xbf3f41fc,0x3f1b02c6,0xbf4bbbf8,0x3f0af1b7,0xbf570348,
0x3ef41f07,0xbf6106f2,0x3ed0eb2a,0xbf69b7e4,0x3f4d9f02,0xbf187fc0,0x3f40d0da,0xbf286605,0x3f32c8c9,0xbf373a23,0x3f239da9,0xbf44e3f5,
0x3f13682a,0xbf514d3d,0x3f0242b1,0xbf5c61c7,0x3ee0924f,0xbf660f88,0x3ebb31a0,0xbf6e46be,0x3f49d112,0xbf1d7fd1,0x3f3c17d9,0xbf2da859,
0x3f2d1469,0xbf3ca003,0x3f1ce11f,0xbf4a4c87,0x3f0b9a6b,0xbf5695e5,0x3ef2bd43,0xbf61668a,0x3ecc9b8b,0xbf6aab7b,0x3ea5129f,0xbf725470,
0x3f45e403,0xbf226799,0x3f373a23,0xbf32c8c9,0x3f273656,0xbf41d870,0x3f15f6d9,0xbf4f7a1f,0x3f039c3d,0xbf5b941a,0x3ee0924f,0xbf660f88,
0x3eb8442a,0xbf6ed89e,0x3e8e9a22,0xbf75dec6,0x3f41d870,0xbf273656,0x3f3238aa,0xbf37c655,0x3f212ff9,0xbf46e22a,0x3f0ee0db,0xbf546b3b,
0x3ef6e0cb,0xbf604621,0x3ece0bea,0xbf6a5ad9,0x3ea395c5,0xbf7294f8,0x3e6fa8b2,0xbf78e3d6,0x3f3daef9,0xbf2beb4a,0x3f2d1469,0xbf3ca003,
0x3f1b02c6,0xbf4bbbf8,0x3f07a136,0xbf591e6a,0x3ee63375,0xbf64aa59,0x3ebb31a0,0xbf6e46be,0x3e8e9a22,0xbf75dec6,0x3e419b37,0xbf7b61fc,
0x3f396842,0xbf3085bb,0x3f27ce61,0xbf4154e1,0x3f14b039,0xbf5064af,0x3f003a06,0xbf5d924d,0x3ed53641,0xbf68bf3c,0x3ea80b1f,0xbf71d19f,
0x3e72b651,0xbf78b47b,0x3e1324ca,0xbf7d57de,0x3ec3ef15,0xbf6c835e,0x3ea09ae5,0xbf731447,0x3e78cfcc,0xbf7853f8,0x3e2f10a2,0xbf7c3b28,
0x3dc8bd36,0xbf7ec46d,0x3cc90ab0,0xbf7fec43,0xbd48fb30,0xbf7fb10f,0xbdfab273,0xbf7e1324,0x3eac7cd4,0xbf710908,0x3e870ada,0xbf76ef5b,
0x3e419b37,0xbf7b61fc,0x3de7fa9a,0xbf7e5a38,0x3d16c32c,0xbf7fd397,0xbd2351cb,0xbf7fcbe2,0xbdee3876,0xbf7e4323,0xbe44b0b9,0xbf7b3bab,
0x3e94a031,0xbf74fa0b,0x3e5a3997,0xbf7a1e84,0x3e09cf86,0xbf7dabcc,0x3d621469,0xbf7f9c18,0xbcc90ab0,0xbf7fec43,0xbdd53db9,0xbf7e9bc9,
0xbe3b6ecf,0xbf7baccd,0xbe8586ce,0xbf772417,0x3e78cfcc,0xbf7853f8,0x3e25c58c,0xbf7c9f8a,0x3da3308c,0xbf7f2f9d,0xbb490fc6,0xbf7fffb1,
0xbdafb680,0xbf7f0e58,0xbe2bf804,0xbf7c5d3a,0xbe7ee6e1,0xbf77f110,0xbea80b1f,0xbf71d19f,0x3e47c5c2,0xbf7b14be,0x3de1bc2e,0xbf7e70b0,
0x3cc90ab0,0xbf7fec43,0xbd7b2b74,0xbf7f84ab,0xbe164083,0xbf7d3aac,0xbe6c9a7f,0xbf791298,0xbea09ae5,0xbf731447,0xbec9b953,0xbf6b4b0c,
0x3e164083,0xbf7d3aac,0x3d6ea038,0xbf7f90b1,0xbcfb49ba,0xbf7fe129,0xbdf475c0,0xbf7e2b72,0xbe541501,0xbf7a7302,0xbe9620d2,0xbf74bf62,
0xbec1071e,0xbf6d1c1d,0xbeea6681,0xbf6398ac,0x3dc8bd36,0xbf7ec46d,0x3bc90f88,0xbf7ffec4,0xbdafb680,0xbf7f0e58,0xbe354098,0xbf7bf531,
0xbe888e93,0xbf76ba07,0xbeb554ec,0xbf6f6830,0xbee0924f,0xbf660f88,0xbf04f484,0xbf5ac450,0x3d48fb30,0xbf7fb10f,0xbd3c6dd5,0xbf7fba9e,
0xbe1008b7,0xbf7d7474,0xbe6fa8b2,0xbf78e3d6,0xbea68f12,0xbf721352,0xbed3c867,0xbf6912ae,0xbeff17b2,0xbf5df6be,0xbf140c5f,0xbf50d937,
0xbe47c5c2,0xbf7b14be,0xbe888e93,0xbf76ba07,0xbeac7cd4,0xbf710908,0xbecf7bca,0xbf6a09a7,0xbef15aea,0xbf61c598,0xbf08f59b,0xbf584853,
0xbf187fc0,0xbf4d9f02,0xbf273656,0xbf41d870,0xbe888e93,0xbf76ba07,0xbeadf73c,0xbf70c501,0xbed25a09,0xbf696591,0xbef58035,0xbf60a6cf,
0xbf0b9a6b,0xbf5695e5,0xbf1ba299,0xbf4b41fa,0xbf2ac082,0xbf3ebc1b,0xbf38dd65,0xbf311722,0xbeac7cd4,0xbf710908,0xbed25a09,0xbf696591,
0xbef6e0cb,0xbf604621,0xbf0cead0,0xbf55b993,0xbf1d7fd1,0xbf49d112,0xbf2d1469,0xbf3ca003,0xbf3b8f3b,0xbf2e3bde,0xbf48d8b3,0xbf1ebc12,
0xbecf7bca,0xbf6a09a7,0xbef58035,0xbf60a6cf,0xbf0cead0,0xbf55b993,0xbf1e1e22,0xbf495521,0xbf2e3bde,0xbf3b8f3b,0xbf3d27b8,0xbf2c800f,
0xbf4ac77f,0xbf1c420c,0xbf570348,0xbf0af1b7,0xbef15aea,0xbf61c598,0xbf0b9a6b,0xbf5695e5,0xbf1d7fd1,0xbf49d112,0xbf2e3bde,0xbf3b8f3b,
0xbf3daef9,0xbf2beb4a,0xbf4bbbf8,0xbf1b02c6,0xbf584853,0xbf08f59b,0xbf633c5a,0xbeebcbbb,0xbf08f59b,0xbf584853,0xbf1ba299,0xbf4b41fa,
0xbf2d1469,0xbf3ca003,0xbf3d27b8,0xbf2c800f,0xbf4bbbf8,0xbf1b02c6,0xbf58b3a1,0xbf084b92,0xbf63f473,0xbee900b7,0xbf6d67a1,0xbebf926f,
0xbf187fc0,0xbf4d9f02,0xbf2ac082,0xbf3ebc1b,0xbf3b8f3b,0xbf2e3bde,0xbf4ac77f,0xbf1c420c,0xbf584853,0xbf08f59b,0xbf63f473,0xbee900b7,
0xbf6db293,0xbebe1d4a,0xbf756d97,0xbe919ddd,0xbf273656,0xbf41d870,0xbf38dd65,0xbf311722,0xbf48d8b3,0xbf1ebc12,0xbf570348,0xbf0af1b7,
0xbf633c5a,0xbeebcbbb,0xbf6d67a1,0xbebf926f,0xbf756d97,0xbe919ddd,0xbf7b3bab,0xbe44b0b9,0xbf3504f3,0xbf3504f3,0xbf41d870,0xbf273656,
0xbf4d9f02,0xbf187fc0,0xbf584853,0xbf08f59b,0xbf61c598,0xbef15aea,0xbf6a09a7,0xbecf7bca,0xbf710908,0xbeac7cd4,0xbf76ba07,0xbe888e93,
0xbf45e403,0xbf226799,0xbf51c0c2,0xbf12c39a,0xbf5c61c7,0xbf0242b1,0xbf65b710,0xbee1fb6a,0xbf6db293,0xbebe1d4a,0xbf74484b,0xbe9920fe,
0xbf796e4e,0xbe667c66,0xbf7d1cdd,0xbe195be0,0xbf54db31,0xbf0e39da,0xbf5f8327,0xbef9a02d,0xbf68bf3c,0xbed53641,0xbf708066,0xbeaf713a,
0xbf76ba07,0xbe888e93,0xbf7b61fc,0xbe419b37,0xbf7e70b0,0xbde1bc2e,0xbf7fe129,0xbcfb49ba,0xbf61c598,0xbef15aea,0xbf6afb8c,0xbecb2aae,
0xbf7294f8,0xbea395c5,0xbf788486,0xbe75c35a,0xbf7cbfc9,0xbe22abb6,0xbf7f3f54,0xbd9cecf9,0xbf7ffec4,0x3bc90f88,0xbf7efcc9,0x3db5f8da,
0xbf6c835e,0xbec3ef15,0xbf740bdd,0xbe9aa086,0xbf79c79d,0xbe605c13,0xbf7dabcc,0xbe09cf86,0xbf7fb10f,0xbd48fb30,0xbf7fd397,0x3d16c32c,
0xbf7e1324,0x3dfab273,0xbf7a7302,0x3e541501,0xbf74fa0b,0xbe94a031,0xbf7a9c59,0xbe5101f1,0xbf7e4323,0xbdee3876,0xbf7fe705,0xbce22a7a,
0xbf7f84ab,0x3d7b2b74,0xbf7d1cdd,0x3e195be0,0xbf78b47b,0x3e72b651,0xbf725470,0x3ea5129f,0xbf7b14be,0xbe47c5c2,0xbf7e9bc9,0xbdd53db9,
0xbf7ffb11,0xbc490e90,0xbf7f2f9d,0x3da3308c,0xbf7c3b28,0x3e2f10a2,0xbf772417,0x3e8586ce,0xbf6ff573,0x3eb263ef,0xbf66becc,0x3eddbe79,
0xbf7ec46d,0xbdc8bd36,0xbf7fffb1,0xbb490fc6,0xbf7eea9d,0x3dbc3ac3,0xbf7b87b2,0x3e3e853e,0xbf75dec6,0x3e8e9a22,0xbf6dfcf2,0x3ebca7af,
0xbf63f473,0x3ee900b7,0xbf57dc7f,0x3f099f4e,0xbf7b14be,0xbe47c5c2,0xbf7e1324,0xbdfab273,0xbf7fb10f,0xbd48fb30,0xbf7fec43,0x3cc90ab0,
0xbf7ec46d,0x3dc8bd36,0xbf7c3b28,0x3e2f10a2,0xbf7853f8,0x3e78cfcc,0xbf731447,0x3ea09ae5,0xbf7f4e6d,0xbd96a905,0xbf7fffb1,0x3b490fc6,
0xbf7f2f9d,0x3da3308c,0xbf7cdf6c,0x3e1f917b,0xbf791298,0x3e6c9a7f,0xbf73ced9,0x3e9c1faf,0xbf6d1c1d,0x3ec1071e,0xbf650479,0x3ee4cbfe,
0xbf7fb10f,0x3d48fb30,0xbf7de0b1,0x3e039502,0xbf7a7302,0x3e541501,0xbf756d97,0x3e919ddd,0xbf6ed89e,0x3eb8442a,0xbf66becc,0x3eddbe79,
0xbf5d2d53,0x3f00e7e4,0xbf5233c6,0x3f121eb0,0xbf7c3b28,0x3e2f10a2,0xbf77beb7,0x3e80f8c0,0xbf718f57,0x3ea986c4,0xbf69b7e4,0x3ed0eb2a,
0xbf604621,0x3ef6e0cb,0xbf554aa4,0x3f0d9281,0xbf48d8b3,0x3f1ebc12,0xbf3b0629,0x3f2ecef7,0xbf74fa0b,0x3e94a031,0xbf6db293,0x3ebe1d4a,
0xbf64aa59,0x3ee63375,0xbf59f26a,0x3f064b82,0xbf4d9f02,0x3f187fc0,0xbf3fc767,0x3f299415,0xbf3085bb,0x3f396842,0xbf1ff6cb,0x3f47de65,
0xbf6a09a7,0x3ecf7bca,0xbf5fe4e9,0x3ef840c8,0xbf53fac3,0x3f0f8784,0xbf466354,0x3f21cbfb,0xbf373a23,0x3f32c8c9,0xbf269de3,0x3f425b89,
0xbf14b039,0x3f5064af,0xbf019573,0x3f5cc7d1,0xbf5b941a,0x3f039c3d,0xbf4e8d90,0x3f173c07,0xbf3fc767,0x3f299415,0xbf2f61a5,0x3f3a7ca4,
0xbf1d7fd1,0x3f49d112,0xbf0a48ad,0x3f577026,0xbeebcbbb,0x3f633c5a,0xbec1071e,0x3f6d1c1d,0xbf49d112,0x3f1d7fd1,0xbf39f2ac,0x3f2ff3e6,
0xbf286605,0x3f40d0da,0xbf1553b7,0x3f4fefa8,0xbf00e7e4,0x3f5d2d53,0xbed6a399,0x3f686b39,0xbea986c4,0x3f718f57,0xbe75c35a,0x3f788486,
0xbf6c835e,0x3ec3ef15,0xbf64aa59,0x3ee63375,0xbf5b941a,0x3f039c3d,0xbf514d3d,0x3f13682a,0xbf45e403,0x3f226799,0xbf396842,0x3f3085bb,
0xbf2beb4a,0x3f3daef9,0xbf1d7fd1,0x3f49d112,0xbf5b941a,0x3f039c3d,0xbf50d937,0x3f140c5f,0xbf44e3f5,0x3f239da9,0xbf37c655,0x3f3238aa,
0xbf299415,0x3f3fc767,0xbf1a6293,0x3f4c3578,0xbf0a48ad,0x3f577026,0xbef2bd43,0x3f61668a,0xbf45e403,0x3f226799,0xbf385216,0x3f31a81d,
0xbf299415,0x3f3fc767,0xbf19c200,0x3f4cae79,0xbf08f59b,0x3f584853,0xbeee9479,0x3f628210,0xbec9b953,0x3f6b4b0c,0xbea395c5,0x3f7294f8,
0xbf2beb4a,0x3f3daef9,0xbf1ba299,0x3f4b41fa,0xbf0a48ad,0x3f577026,0xbeeff7fb,0x3f62241a,0xbec9b953,0x3f6b4b0c,0xbea21887,0x3f72d4eb,
0xbe72b651,0x3f78b47b,0xbe1f917b,0x3f7cdf6c,0xbf0e39da,0x3f54db31,0xbef6e0cb,0x3f604621,0xbecf7bca,0x3f6a09a7,0xbea68f12,0x3f721352,
0xbe78cfcc,0x3f7853f8,0xbe22abb6,0x3f7cbfc9,0xbd96a905,0x3f7f4e6d,0x3c490e90,0x3f7ffb11,0xbedae880,0x3f676bd8,0xbeb0eacb,0x3f703b37,
0xbe8586ce,0x3f772417,0xbe3228d4,0x3f7c187a,0xbdafb680,0x3f7f0e58,0x3b490fc6,0x3f7fffb1,0x3dbc3ac3,0x3f7eea9d,0x3e3857ec,0x3f7bd14d,
0xbe94a031,0x3f74fa0b,0xbe4dee60,0x3f7ac516,0xbde1bc2e,0x3f7e70b0,0xbc96c9b6,0x3f7ff4e6,0x3d96a905,0x3f7f4e6d,0x3e28defc,0x3f7c7eb0,
0x3e827dc0,0x3f778bc5,0x3eaf713a,0x3f708066,0xbe164083,0x3f7d3aac,0xbd55880e,0x3f7fa6e3,0x3d2fe007,0x3f7fc38f,0x3e0cec4a,0x3f7d906e,
0x3e6c9a7f,0x3f791298,0x3ea5129f,0x3f725470,0x3ed25a09,0x3f696591,0x3efdbabb,0x3f5e5aa6,0xbf0e39da,0x3f54db31,0xbefc5d27,0x3f5ebe05,
0xbedae880,0x3f676bd8,0xbeb8442a,0x3f6ed89e,0xbe94a031,0x3f74fa0b,0xbe605c13,0x3f79c79d,0xbe164083,0x3f7d3aac,0xbd96a905,0x3f7f4e6d,
0xbecf7bca,0x3f6a09a7,0xbeab0201,0x3f714c7a,0xbe8586ce,0x3f772417,0xbe3e853e,0x3f7b87b2,0xbde1bc2e,0x3f7e70b0,0xbd0a342f,0x3f7fdaaf,
0x3d2fe007,0x3f7fc38f,0x3df475c0,0x3f7e2b72,0xbe78cfcc,0x3f7853f8,0xbe28defc,0x3f7c7eb0,0xbdafb680,0x3f7f0e58,0xbbc90f88,0x3f7ffec4,
0x3d96a905,0x3f7f4e6d,0x3e1c76de,0x3f7cfe73,0x3e6c9a7f,0x3f791298,0x3e9d9e78,0x3f73913f,0xbd96a905,0x3f7f4e6d,0x3c16cb58,0x3f7ffd39,
0x3dbc3ac3,0x3f7eea9d,0x3e3228d4,0x3f7c187a,0x3e827dc0,0x3f778bc5,0x3eab0201,0x3f714c7a,0x3ed25a09,0x3f696591,0x3ef840c8,0x3f5fe4e9,
0x3dc8bd36,0x3f7ec46d,0x3e3b6ecf,0x3f7baccd,0x3e888e93,0x3f76ba07,0x3eb263ef,0x3f6ff573,0x3edae880,0x3f676bd8,0x3f00e7e4,0x3f5d2d53,
0x3f13682a,0x3f514d3d,0x3f24d225,0x3f43e200,0x3e888e93,0x3f76ba07,0x3eb3dca5,0x3f6faf1b,0x3eddbe79,0x3f66becc,0x3f02ef9f,0x3f5bfb34,
0x3f15f6d9,0x3f4f7a1f,0x3f27ce61,0x3f4154e1,0x3f385216,0x3f31a81d,0x3f476085,0x3f209393,0x3edae880,0x3f676bd8,0x3f0242b1,0x3f5c61c7,
0x3f15f6d9,0x3f4f7a1f,0x3f286605,0x3f40d0da,0x3f396842,0x3f3085bb,0x3f48d8b3,0x3f1ebc12,0x3f5695e5,0x3f0b9a6b,0x3f628210,0x3eee9479,
0x3f13682a,0x3f514d3d,0x3f269de3,0x3f425b89,0x3f385216,0x3f31a81d,0x3f485bca,0x3f1f599f,0x3f5695e5,0x3f0b9a6b,0x3f62df7b,0x3eed3063,
0x3f6d1c1d,0x3ec1071e,0x3f75341d,0x3e931f35,
};
__device__ __align__(128) const uint32_t T_a1[2048] = {
0x3f803f80,0x0,0x3f803f80,0x0,0x3f803f80,0x0,0x3f803f80,0x0,0x3f803f80,0x0,0x3f803f80,0x0,
0x3f803f80,0x0,0x3f803f80,0x0,0x3f7b3f80,0xbe480000,0xbe480000,0xbf7bbf80,0x3f553f6d,0xbf0ebec4,0xbf0ebec4,0xbf55bf6d,
0x3f0e3f35,0xbf55bf35,0xbf55bf35,0xbf0ebf35,0x3e483ec4,0xbf7bbf6d,0xbf7bbf6d,0xbe48bec4,0x3f6d3f80,0xbec40000,0xbf6dbf80,0x3ec40000,
0x3ec43f35,0xbf6dbf35,0xbec4bf35,0x3f6d3f35,0xbec40000,0xbf6dbf80,0x3ec40000,0x3f6d3f80,0xbf6dbf35,0xbec4bf35,0x3f6d3f35,0x3ec43f35,
0x3f553f80,0xbf0e0000,0x3f0e0000,0x3f553f80,0xbe483ec4,0xbf7bbf6d,0x3f7b3f6d,0xbe483ec4,0xbf7bbf35,0xbe48bf35,0x3e483f35,0xbf7bbf35,
0xbf0ebf6d,0x3f553ec4,0xbf55bec4,0xbf0ebf6d,0x3f353f80,0xbf350000,0x3f353f80,0xbf350000,0xbf350000,0xbf35bf80,0xbf350000,0xbf35bf80,
0xbf35bf80,0x3f350000,0xbf35bf80,0x3f350000,0x3f350000,0x3f353f80,0x3f350000,0x3f353f80,0x3f0e3f80,0xbf550000,0xbf550000,0xbf0ebf80,
0xbf7bbec4,0xbe48bf6d,0xbe48bf6d,0x3f7b3ec4,0x3e48bf35,0x3f7b3f35,0x3f7b3f35,0xbe483f35,0x3f553f6d,0xbf0e3ec4,0xbf0e3ec4,0xbf55bf6d,
0x3ec43f80,0xbf6d0000,0xbec4bf80,0x3f6d0000,0xbf6dbf35,0x3ec4bf35,0x3f6d3f35,0xbec43f35,0x3f6d0000,0x3ec43f80,0xbf6d0000,0xbec4bf80,
0xbec43f35,0xbf6dbf35,0x3ec4bf35,0x3f6d3f35,0x3e483f80,0xbf7b0000,0x3f7b0000,0x3e483f80,0xbf0ebf6d,0x3f55bec4,0xbf553ec4,0xbf0ebf6d,
0x3f553f35,0xbf0e3f35,0x3f0ebf35,0x3f553f35,0xbf7bbec4,0x3e48bf6d,0xbe483f6d,0xbf7bbec4,0x3f80,0xbf800000,0x3f80,0xbf800000,
0xbf80,0x3f800000,0xbf80,0x3f800000,0x3f80,0xbf800000,0x3f80,0xbf800000,0xbf80,0x3f800000,0xbf80,0x3f800000,
0xbe483f80,0xbf7b0000,0xbf7b0000,0x3e48bf80,0x3f0ebf6d,0x3f553ec4,0x3f553ec4,0xbf0e3f6d,0xbf553f35,0xbf0ebf35,0xbf0ebf35,0x3f55bf35,
0x3f7bbec4,0x3e483f6d,0x3e483f6d,0xbf7b3ec4,0xbec43f80,0xbf6d0000,0x3ec4bf80,0x3f6d0000,0x3f6dbf35,0x3ec43f35,0xbf6d3f35,0xbec4bf35,
0xbf6d0000,0x3ec4bf80,0x3f6d0000,0xbec43f80,0x3ec43f35,0xbf6d3f35,0xbec4bf35,0x3f6dbf35,0xbf0e3f80,0xbf550000,0x3f550000,0xbf0e3f80,
0x3f7bbec4,0xbe483f6d,0x3e48bf6d,0x3f7bbec4,0xbe48bf35,0x3f7bbf35,0xbf7b3f35,0xbe48bf35,0xbf553f6d,0xbf0ebec4,0x3f0e3ec4,0xbf553f6d,
0xbf353f80,0xbf350000,0xbf353f80,0xbf350000,0x3f350000,0xbf353f80,0x3f350000,0xbf353f80,0x3f35bf80,0x3f350000,0x3f35bf80,0x3f350000,
0xbf350000,0x3f35bf80,0xbf350000,0x3f35bf80,0xbf553f80,0xbf0e0000,0xbf0e0000,0x3f55bf80,0x3e483ec4,0xbf7b3f6d,0xbf7b3f6d,0xbe48bec4,
0x3f7bbf35,0xbe483f35,0xbe483f35,0xbf7b3f35,0x3f0ebf6d,0x3f55bec4,0x3f55bec4,0xbf0e3f6d,0xbf6d3f80,0xbec40000,0x3f6dbf80,0x3ec40000,
0xbec43f35,0xbf6d3f35,0x3ec4bf35,0x3f6dbf35,0x3ec40000,0xbf6d3f80,0xbec40000,0x3f6dbf80,0x3f6dbf35,0xbec43f35,0xbf6d3f35,0x3ec4bf35,
0xbf7b3f80,0xbe480000,0x3e480000,0xbf7b3f80,0xbf553f6d,0xbf0e3ec4,0x3f0ebec4,0xbf553f6d,0xbf0e3f35,0xbf553f35,0x3f55bf35,0xbf0e3f35,
0xbe483ec4,0xbf7b3f6d,0x3f7bbf6d,0xbe483ec4,0xbf803f80,0x0,0xbf803f80,0x0,0xbf803f80,0x0,0xbf803f80,0x0,
0xbf803f80,0x0,0xbf803f80,0x0,0xbf803f80,0x0,0xbf803f80,0x0,0xbf7b3f80,0x3e480000,0x3e480000,0x3f7bbf80,
0xbf553f6d,0x3f0ebec4,0x3f0ebec4,0x3f55bf6d,0xbf0e3f35,0x3f55bf35,0x3f55bf35,0x3f0ebf35,0xbe483ec4,0x3f7bbf6d,0x3f7bbf6d,0x3e48bec4,
0xbf6d3f80,0x3ec40000,0x3f6dbf80,0xbec40000,0xbec43f35,0x3f6dbf35,0x3ec4bf35,0xbf6d3f35,0x3ec40000,0x3f6dbf80,0xbec40000,0xbf6d3f80,
0x3f6dbf35,0x3ec4bf35,0xbf6d3f35,0xbec43f35,0xbf553f80,0x3f0e0000,0xbf0e0000,0xbf553f80,0x3e483ec4,0x3f7bbf6d,0xbf7b3f6d,0x3e483ec4,
0x3f7bbf35,0x3e48bf35,0xbe483f35,0x3f7bbf35,0x3f0ebf6d,0xbf553ec4,0x3f55bec4,0x3f0ebf6d,0xbf353f80,0x3f350000,0xbf353f80,0x3f350000,
0x3f350000,0x3f35bf80,0x3f350000,0x3f35bf80,0x3f35bf80,0xbf350000,0x3f35bf80,0xbf350000,0xbf350000,0xbf353f80,0xbf350000,0xbf353f80,
0xbf0e3f80,0x3f550000,0x3f550000,0x3f0ebf80,0x3f7bbec4,0x3e48bf6d,0x3e48bf6d,0xbf7b3ec4,0xbe48bf35,0xbf7b3f35,0xbf7b3f35,0x3e483f35,
0xbf553f6d,0x3f0e3ec4,0x3f0e3ec4,0x3f55bf6d,0xbec43f80,0x3f6d0000,0x3ec4bf80,0xbf6d0000,0x3f6dbf35,0xbec4bf35,0xbf6d3f35,0x3ec43f35,
0xbf6d0000,0xbec43f80,0x3f6d0000,0x3ec4bf80,0x3ec43f35,0x3f6dbf35,0xbec4bf35,0xbf6d3f35,0xbe483f80,0x3f7b0000,0xbf7b0000,0xbe483f80,
0x3f0ebf6d,0xbf55bec4,0x3f553ec4,0x3f0ebf6d,0xbf553f35,0x3f0e3f35,0xbf0ebf35,0xbf553f35,0x3f7bbec4,0xbe48bf6d,0x3e483f6d,0x3f7bbec4,
0x3f80,0x3f800000,0x3f80,0x3f800000,0xbf80,0xbf800000,0xbf80,0xbf800000,0x3f80,0x3f800000,0x3f80,0x3f800000,
0xbf80,0xbf800000,0xbf80,0xbf800000,0x3e483f80,0x3f7b0000,0x3f7b0000,0xbe48bf80,0xbf0ebf6d,0xbf553ec4,0xbf553ec4,0x3f0e3f6d,
0x3f553f35,0x3f0ebf35,0x3f0ebf35,0xbf55bf35,0xbf7bbec4,0xbe483f6d,0xbe483f6d,0x3f7b3ec4,0x3ec43f80,0x3f6d0000,0xbec4bf80,0xbf6d0000,
0xbf6dbf35,0xbec43f35,0x3f6d3f35,0x3ec4bf35,0x3f6d0000,0xbec4bf80,0xbf6d0000,0x3ec43f80,0xbec43f35,0x3f6d3f35,0x3ec4bf35,0xbf6dbf35,
0x3f0e3f80,0x3f550000,0xbf550000,0x3f0e3f80,0xbf7bbec4,0x3e483f6d,0xbe48bf6d,0xbf7bbec4,0x3e48bf35,0xbf7bbf35,0x3f7b3f35,0x3e48bf35,
0x3f553f6d,0x3f0ebec4,0xbf0e3ec4,0x3f553f6d,0x3f353f80,0x3f350000,0x3f353f80,0x3f350000,0xbf350000,0x3f353f80,0xbf350000,0x3f353f80,
0xbf35bf80,0xbf350000,0xbf35bf80,0xbf350000,0x3f350000,0xbf35bf80,0x3f350000,0xbf35bf80,0x3f553f80,0x3f0e0000,0x3f0e0000,0xbf55bf80,
0xbe483ec4,0x3f7b3f6d,0x3f7b3f6d,0x3e48bec4,0xbf7bbf35,0x3e483f35,0x3e483f35,0x3f7b3f35,0xbf0ebf6d,0xbf55bec4,0xbf55bec4,0x3f0e3f6d,
0x3f6d3f80,0x3ec40000,0xbf6dbf80,0xbec40000,0x3ec43f35,0x3f6d3f35,0xbec4bf35,0xbf6dbf35,0xbec40000,0x3f6d3f80,0x3ec40000,0xbf6dbf80,
0xbf6dbf35,0x3ec43f35,0x3f6d3f35,0xbec4bf35,0x3f7b3f80,0x3e480000,0xbe480000,0x3f7b3f80,0x3f553f6d,0x3f0e3ec4,0xbf0ebec4,0x3f553f6d,
0x3f0e3f35,0x3f553f35,0xbf55bf35,0x3f0e3f35,0x3e483ec4,0x3f7b3f6d,0xbf7bbf6d,0x3e483ec4,0x3f803f80,0x0,0x3f803f80,0x0,
0x3f803f80,0x0,0x3f803f80,0x0,0x3f803f80,0x0,0x3f803f80,0x0,0x3f803f80,0x0,0x3f803f80,0x0,
0xbf7bbf80,0x3e480000,0x3e480000,0x3f7b3f80,0xbf55bf6d,0x3f0e3ec4,0x3f0e3ec4,0x3f553f6d,0xbf0ebf35,0x3f553f35,0x3f553f35,0x3f0e3f35,
0xbe48bec4,0x3f7b3f6d,0x3f7b3f6d,0x3e483ec4,0x3f6d3f80,0xbec40000,0xbf6dbf80,0x3ec40000,0x3ec43f35,0xbf6dbf35,0xbec4bf35,0x3f6d3f35,
0xbec40000,0xbf6dbf80,0x3ec40000,0x3f6d3f80,0xbf6dbf35,0xbec4bf35,0x3f6d3f35,0x3ec43f35,0xbf55bf80,0x3f0e0000,0xbf0e0000,0xbf55bf80,
0x3e48bec4,0x3f7b3f6d,0xbf7bbf6d,0x3e48bec4,0x3f7b3f35,0x3e483f35,0xbe48bf35,0x3f7b3f35,0x3f0e3f6d,0xbf55bec4,0x3f553ec4,0x3f0e3f6d,
0x3f353f80,0xbf350000,0x3f353f80,0xbf350000,0xbf350000,0xbf35bf80,0xbf350000,0xbf35bf80,0xbf35bf80,0x3f350000,0xbf35bf80,0x3f350000,
0x3f350000,0x3f353f80,0x3f350000,0x3f353f80,0xbf0ebf80,0x3f550000,0x3f550000,0x3f0e3f80,0x3f7b3ec4,0x3e483f6d,0x3e483f6d,0xbf7bbec4,
0xbe483f35,0xbf7bbf35,0xbf7bbf35,0x3e48bf35,0xbf55bf6d,0x3f0ebec4,0x3f0ebec4,0x3f553f6d,0x3ec43f80,0xbf6d0000,0xbec4bf80,0x3f6d0000,
0xbf6dbf35,0x3ec4bf35,0x3f6d3f35,0xbec43f35,0x3f6d0000,0x3ec43f80,0xbf6d0000,0xbec4bf80,0xbec43f35,0xbf6dbf35,0x3ec4bf35,0x3f6d3f35,
0xbe48bf80,0x3f7b0000,0xbf7b0000,0xbe48bf80,0x3f0e3f6d,0xbf553ec4,0x3f55bec4,0x3f0e3f6d,0xbf55bf35,0x3f0ebf35,0xbf0e3f35,0xbf55bf35,
0x3f7b3ec4,0xbe483f6d,0x3e48bf6d,0x3f7b3ec4,0x3f80,0xbf800000,0x3f80,0xbf800000,0xbf80,0x3f800000,0xbf80,0x3f800000,
0x3f80,0xbf800000,0x3f80,0xbf800000,0xbf80,0x3f800000,0xbf80,0x3f800000,0x3e48bf80,0x3f7b0000,0x3f7b0000,0xbe483f80,
0xbf0e3f6d,0xbf55bec4,0xbf55bec4,0x3f0ebf6d,0x3f55bf35,0x3f0e3f35,0x3f0e3f35,0xbf553f35,0xbf7b3ec4,0xbe48bf6d,0xbe48bf6d,0x3f7bbec4,
0xbec43f80,0xbf6d0000,0x3ec4bf80,0x3f6d0000,0x3f6dbf35,0x3ec43f35,0xbf6d3f35,0xbec4bf35,0xbf6d0000,0x3ec4bf80,0x3f6d0000,0xbec43f80,
0x3ec43f35,0xbf6d3f35,0xbec4bf35,0x3f6dbf35,0x3f0ebf80,0x3f550000,0xbf550000,0x3f0ebf80,0xbf7b3ec4,0x3e48bf6d,0xbe483f6d,0xbf7b3ec4,
0x3e483f35,0xbf7b3f35,0x3f7bbf35,0x3e483f35,0x3f55bf6d,0x3f0e3ec4,0xbf0ebec4,0x3f55bf6d,0xbf353f80,0xbf350000,0xbf353f80,0xbf350000,
0x3f350000,0xbf353f80,0x3f350000,0xbf353f80,0x3f35bf80,0x3f350000,0x3f35bf80,0x3f350000,0xbf350000,0x3f35bf80,0xbf350000,0x3f35bf80,
0x3f55bf80,0x3f0e0000,0x3f0e0000,0xbf553f80,0xbe48bec4,0x3f7bbf6d,0x3f7bbf6d,0x3e483ec4,0xbf7b3f35,0x3e48bf35,0x3e48bf35,0x3f7bbf35,
0xbf0e3f6d,0xbf553ec4,0xbf553ec4,0x3f0ebf6d,0xbf6d3f80,0xbec40000,0x3f6dbf80,0x3ec40000,0xbec43f35,0xbf6d3f35,0x3ec4bf35,0x3f6dbf35,
0x3ec40000,0xbf6d3f80,0xbec40000,0x3f6dbf80,0x3f6dbf35,0xbec43f35,0xbf6d3f35,0x3ec4bf35,0x3f7bbf80,0x3e480000,0xbe480000,0x3f7bbf80,
0x3f55bf6d,0x3f0ebec4,0xbf0e3ec4,0x3f55bf6d,0x3f0ebf35,0x3f55bf35,0xbf553f35,0x3f0ebf35,0x3e48bec4,0x3f7bbf6d,0xbf7b3f6d,0x3e48bec4,
0xbf803f80,0x0,0xbf803f80,0x0,0xbf803f80,0x0,0xbf803f80,0x0,0xbf803f80,0x0,0xbf803f80,0x0,
0xbf803f80,0x0,0xbf803f80,0x0,0x3f7bbf80,0xbe480000,0xbe480000,0xbf7b3f80,0x3f55bf6d,0xbf0e3ec4,0xbf0e3ec4,0xbf553f6d,
0x3f0ebf35,0xbf553f35,0xbf553f35,0xbf0e3f35,0x3e48bec4,0xbf7b3f6d,0xbf7b3f6d,0xbe483ec4,0xbf6d3f80,0x3ec40000,0x3f6dbf80,0xbec40000,
0xbec43f35,0x3f6dbf35,0x3ec4bf35,0xbf6d3f35,0x3ec40000,0x3f6dbf80,0xbec40000,0xbf6d3f80,0x3f6dbf35,0x3ec4bf35,0xbf6d3f35,0xbec43f35,
0x3f55bf80,0xbf0e0000,0x3f0e0000,0x3f55bf80,0xbe48bec4,0xbf7b3f6d,0x3f7bbf6d,0xbe48bec4,0xbf7b3f35,0xbe483f35,0x3e48bf35,0xbf7b3f35,
0xbf0e3f6d,0x3f55bec4,0xbf553ec4,0xbf0e3f6d,0xbf353f80,0x3f350000,0xbf353f80,0x3f350000,0x3f350000,0x3f35bf80,0x3f350000,0x3f35bf80,
0x3f35bf80,0xbf350000,0x3f35bf80,0xbf350000,0xbf350000,0xbf353f80,0xbf350000,0xbf353f80,0x3f0ebf80,0xbf550000,0xbf550000,0xbf0e3f80,
0xbf7b3ec4,0xbe483f6d,0xbe483f6d,0x3f7bbec4,0x3e483f35,0x3f7bbf35,0x3f7bbf35,0xbe48bf35,0x3f55bf6d,0xbf0ebec4,0xbf0ebec4,0xbf553f6d,
0xbec43f80,0x3f6d0000,0x3ec4bf80,0xbf6d0000,0x3f6dbf35,0xbec4bf35,0xbf6d3f35,0x3ec43f35,0xbf6d0000,0xbec43f80,0x3f6d0000,0x3ec4bf80,
0x3ec43f35,0x3f6dbf35,0xbec4bf35,0xbf6d3f35,0x3e48bf80,0xbf7b0000,0x3f7b0000,0x3e48bf80,0xbf0e3f6d,0x3f553ec4,0xbf55bec4,0xbf0e3f6d,
0x3f55bf35,0xbf0ebf35,0x3f0e3f35,0x3f55bf35,0xbf7b3ec4,0x3e483f6d,0xbe48bf6d,0xbf7b3ec4,0x3f80,0x3f800000,0x3f80,0x3f800000,
0xbf80,0xbf800000,0xbf80,0xbf800000,0x3f80,0x3f800000,0x3f80,0x3f800000,0xbf80,0xbf800000,0xbf80,0xbf800000,
0xbe48bf80,0xbf7b0000,0xbf7b0000,0x3e483f80,0x3f0e3f6d,0x3f55bec4,0x3f55bec4,0xbf0ebf6d,0xbf55bf35,0xbf0e3f35,0xbf0e3f35,0x3f553f35,
0x3f7b3ec4,0x3e48bf6d,0x3e48bf6d,0xbf7bbec4,0x3ec43f80,0x3f6d0000,0xbec4bf80,0xbf6d0000,0xbf6dbf35,0xbec43f35,0x3f6d3f35,0x3ec4bf35,
0x3f6d0000,0xbec4bf80,0xbf6d0000,0x3ec43f80,0xbec43f35,0x3f6d3f35,0x3ec4bf35,0xbf6dbf35,0xbf0ebf80,0xbf550000,0x3f550000,0xbf0ebf80,
0x3f7b3ec4,0xbe48bf6d,0x3e483f6d,0x3f7b3ec4,0xbe483f35,0x3f7b3f35,0xbf7bbf35,0xbe483f35,0xbf55bf6d,0xbf0e3ec4,0x3f0ebec4,0xbf55bf6d,
0x3f353f80,0x3f350000,0x3f353f80,0x3f350000,0xbf350000,0x3f353f80,0xbf350000,0x3f353f80,0xbf35bf80,0xbf350000,0xbf35bf80,0xbf350000,
0x3f350000,0xbf35bf80,0x3f350000,0xbf35bf80,0xbf55bf80,0xbf0e0000,0xbf0e0000,0x3f553f80,0x3e48bec4,0xbf7bbf6d,0xbf7bbf6d,0xbe483ec4,
0x3f7b3f35,0xbe48bf35,0xbe48bf35,0xbf7bbf35,0x3f0e3f6d,0x3f553ec4,0x3f553ec4,0xbf0ebf6d,0x3f6d3f80,0x3ec40000,0xbf6dbf80,0xbec40000,
0x3ec43f35,0x3f6d3f35,0xbec4bf35,0xbf6dbf35,0xbec40000,0x3f6d3f80,0x3ec40000,0xbf6dbf80,0xbf6dbf35,0x3ec43f35,0x3f6d3f35,0xbec4bf35,
0xbf7bbf80,0xbe480000,0x3e480000,0xbf7bbf80,0xbf55bf6d,0xbf0ebec4,0x3f0e3ec4,0xbf55bf6d,0xbf0ebf35,0xbf55bf35,0x3f553f35,0xbf0ebf35,
0xbe48bec4,0xbf7bbf6d,0x3f7b3f6d,0xbe48bec4,0x0,0x3f803f80,0x0,0x3f803f80,0x0,0x3f803f80,0x0,0x3f803f80,
0x0,0x3f803f80,0x0,0x3f803f80,0x0,0x3f803f80,0x0,0x3f803f80,0x3e480000,0x3f7b3f80,0x3f7b3f80,0xbe480000,
0x3f0e3ec4,0x3f553f6d,0x3f553f6d,0xbf0ebec4,0x3f553f35,0x3f0e3f35,0x3f0e3f35,0xbf55bf35,0x3f7b3f6d,0x3e483ec4,0x3e483ec4,0xbf7bbf6d,
0x3ec40000,0x3f6d3f80,0xbec40000,0xbf6dbf80,0x3f6d3f35,0x3ec43f35,0xbf6dbf35,0xbec4bf35,0x3f6d3f80,0xbec40000,0xbf6dbf80,0x3ec40000,
0x3ec43f35,0xbf6dbf35,0xbec4bf35,0x3f6d3f35,0x3f0e0000,0x3f553f80,0xbf55bf80,0x3f0e0000,0x3f7b3f6d,0xbe483ec4,0x3e48bec4,0x3f7b3f6d,
0x3e483f35,0xbf7bbf35,0x3f7b3f35,0x3e483f35,0xbf55bec4,0xbf0ebf6d,0x3f0e3f6d,0xbf55bec4,0x3f350000,0x3f353f80,0x3f350000,0x3f353f80,
0x3f353f80,0xbf350000,0x3f353f80,0xbf350000,0xbf350000,0xbf35bf80,0xbf350000,0xbf35bf80,0xbf35bf80,0x3f350000,0xbf35bf80,0x3f350000,
0x3f550000,0x3f0e3f80,0x3f0e3f80,0xbf550000,0x3e483f6d,0xbf7bbec4,0xbf7bbec4,0xbe48bf6d,0xbf7bbf35,0x3e48bf35,0x3e48bf35,0x3f7b3f35,
0x3f0ebec4,0x3f553f6d,0x3f553f6d,0xbf0e3ec4,0x3f6d0000,0x3ec43f80,0xbf6d0000,0xbec4bf80,0xbec43f35,0xbf6dbf35,0x3ec4bf35,0x3f6d3f35,
0xbec4bf80,0x3f6d0000,0x3ec43f80,0xbf6d0000,0x3f6d3f35,0xbec43f35,0xbf6dbf35,0x3ec4bf35,0x3f7b0000,0x3e483f80,0xbe48bf80,0x3f7b0000,
0xbf553ec4,0xbf0ebf6d,0x3f0e3f6d,0xbf553ec4,0x3f0ebf35,0x3f553f35,0xbf55bf35,0x3f0ebf35,0xbe483f6d,0xbf7bbec4,0x3f7b3ec4,0xbe483f6d,
0x3f800000,0x3f80,0x3f800000,0x3f80,0xbf800000,0xbf80,0xbf800000,0xbf80,0x3f800000,0x3f80,0x3f800000,0x3f80,
0xbf800000,0xbf80,0xbf800000,0xbf80,0x3f7b0000,0xbe483f80,0xbe483f80,0xbf7b0000,0xbf55bec4,0x3f0ebf6d,0x3f0ebf6d,0x3f553ec4,
0x3f0e3f35,0xbf553f35,0xbf553f35,0xbf0ebf35,0xbe48bf6d,0x3f7bbec4,0x3f7bbec4,0x3e483f6d,0x3f6d0000,0xbec43f80,0xbf6d0000,0x3ec4bf80,
0xbec4bf35,0x3f6dbf35,0x3ec43f35,0xbf6d3f35,0xbec43f80,0xbf6d0000,0x3ec4bf80,0x3f6d0000,0x3f6dbf35,0x3ec43f35,0xbf6d3f35,0xbec4bf35,
0x3f550000,0xbf0e3f80,0x3f0ebf80,0x3f550000,0x3e48bf6d,0x3f7bbec4,0xbf7b3ec4,0x3e48bf6d,0xbf7b3f35,0xbe48bf35,0x3e483f35,0xbf7b3f35,
0x3f0e3ec4,0xbf553f6d,0x3f55bf6d,0x3f0e3ec4,0x3f350000,0xbf353f80,0x3f350000,0xbf353f80,0x3f35bf80,0x3f350000,0x3f35bf80,0x3f350000,
0xbf350000,0x3f35bf80,0xbf350000,0x3f35bf80,0xbf353f80,0xbf350000,0xbf353f80,0xbf350000,0x3f0e0000,0xbf553f80,0xbf553f80,0xbf0e0000,
0x3f7bbf6d,0x3e483ec4,0x3e483ec4,0xbf7b3f6d,0x3e48bf35,0x3f7bbf35,0x3f7bbf35,0xbe483f35,0xbf553ec4,0x3f0ebf6d,0x3f0ebf6d,0x3f55bec4,
0x3ec40000,0xbf6d3f80,0xbec40000,0x3f6dbf80,0x3f6dbf35,0xbec43f35,0xbf6d3f35,0x3ec4bf35,0x3f6dbf80,0x3ec40000,0xbf6d3f80,0xbec40000,
0x3ec4bf35,0x3f6dbf35,0xbec43f35,0xbf6d3f35,0x3e480000,0xbf7b3f80,0x3f7bbf80,0x3e480000,0x3f0ebec4,0xbf553f6d,0x3f55bf6d,0x3f0ebec4,
0x3f55bf35,0xbf0e3f35,0x3f0ebf35,0x3f55bf35,0x3f7bbf6d,0xbe483ec4,0x3e48bec4,0x3f7bbf6d,0x0,0xbf803f80,0x0,0xbf803f80,
0x0,0xbf803f80,0x0,0xbf803f80,0x0,0xbf803f80,0x0,0xbf803f80,0x0,0xbf803f80,0x0,0xbf803f80,
0xbe480000,0xbf7b3f80,0xbf7b3f80,0x3e480000,0xbf0e3ec4,0xbf553f6d,0xbf553f6d,0x3f0ebec4,0xbf553f35,0xbf0e3f35,0xbf0e3f35,0x3f55bf35,
0xbf7b3f6d,0xbe483ec4,0xbe483ec4,0x3f7bbf6d,0xbec40000,0xbf6d3f80,0x3ec40000,0x3f6dbf80,0xbf6d3f35,0xbec43f35,0x3f6dbf35,0x3ec4bf35,
0xbf6d3f80,0x3ec40000,0x3f6dbf80,0xbec40000,0xbec43f35,0x3f6dbf35,0x3ec4bf35,0xbf6d3f35,0xbf0e0000,0xbf553f80,0x3f55bf80,0xbf0e0000,
0xbf7b3f6d,0x3e483ec4,0xbe48bec4,0xbf7b3f6d,0xbe483f35,0x3f7bbf35,0xbf7b3f35,0xbe483f35,0x3f55bec4,0x3f0ebf6d,0xbf0e3f6d,0x3f55bec4,
0xbf350000,0xbf353f80,0xbf350000,0xbf353f80,0xbf353f80,0x3f350000,0xbf353f80,0x3f350000,0x3f350000,0x3f35bf80,0x3f350000,0x3f35bf80,
0x3f35bf80,0xbf350000,0x3f35bf80,0xbf350000,0xbf550000,0xbf0e3f80,0xbf0e3f80,0x3f550000,0xbe483f6d,0x3f7bbec4,0x3f7bbec4,0x3e48bf6d,
0x3f7bbf35,0xbe48bf35,0xbe48bf35,0xbf7b3f35,0xbf0ebec4,0xbf553f6d,0xbf553f6d,0x3f0e3ec4,0xbf6d0000,0xbec43f80,0x3f6d0000,0x3ec4bf80,
0x3ec43f35,0x3f6dbf35,0xbec4bf35,0xbf6d3f35,0x3ec4bf80,0xbf6d0000,0xbec43f80,0x3f6d0000,0xbf6d3f35,0x3ec43f35,0x3f6dbf35,0xbec4bf35,
0xbf7b0000,0xbe483f80,0x3e48bf80,0xbf7b0000,0x3f553ec4,0x3f0ebf6d,0xbf0e3f6d,0x3f553ec4,0xbf0ebf35,0xbf553f35,0x3f55bf35,0xbf0ebf35,
0x3e483f6d,0x3f7bbec4,0xbf7b3ec4,0x3e483f6d,0xbf800000,0x3f80,0xbf800000,0x3f80,0x3f800000,0xbf80,0x3f800000,0xbf80,
0xbf800000,0x3f80,0xbf800000,0x3f80,0x3f800000,0xbf80,0x3f800000,0xbf80,0xbf7b0000,0x3e483f80,0x3e483f80,0x3f7b0000,
0x3f55bec4,0xbf0ebf6d,0xbf0ebf6d,0xbf553ec4,0xbf0e3f35,0x3f553f35,0x3f553f35,0x3f0ebf35,0x3e48bf6d,0xbf7bbec4,0xbf7bbec4,0xbe483f6d,
0xbf6d0000,0x3ec43f80,0x3f6d0000,0xbec4bf80,0x3ec4bf35,0xbf6dbf35,0xbec43f35,0x3f6d3f35,0x3ec43f80,0x3f6d0000,0xbec4bf80,0xbf6d0000,
0xbf6dbf35,0xbec43f35,0x3f6d3f35,0x3ec4bf35,0xbf550000,0x3f0e3f80,0xbf0ebf80,0xbf550000,0xbe48bf6d,0xbf7bbec4,0x3f7b3ec4,0xbe48bf6d,
0x3f7b3f35,0x3e48bf35,0xbe483f35,0x3f7b3f35,0xbf0e3ec4,0x3f553f6d,0xbf55bf6d,0xbf0e3ec4,0xbf350000,0x3f353f80,0xbf350000,0x3f353f80,
0xbf35bf80,0xbf350000,0xbf35bf80,0xbf350000,0x3f350000,0xbf35bf80,0x3f350000,0xbf35bf80,0x3f353f80,0x3f350000,0x3f353f80,0x3f350000,
0xbf0e0000,0x3f553f80,0x3f553f80,0x3f0e0000,0xbf7bbf6d,0xbe483ec4,0xbe483ec4,0x3f7b3f6d,0xbe48bf35,0xbf7bbf35,0xbf7bbf35,0x3e483f35,
0x3f553ec4,0xbf0ebf6d,0xbf0ebf6d,0xbf55bec4,0xbec40000,0x3f6d3f80,0x3ec40000,0xbf6dbf80,0xbf6dbf35,0x3ec43f35,0x3f6d3f35,0xbec4bf35,
0xbf6dbf80,0xbec40000,0x3f6d3f80,0x3ec40000,0xbec4bf35,0xbf6dbf35,0x3ec43f35,0x3f6d3f35,0xbe480000,0x3f7b3f80,0xbf7bbf80,0xbe480000,
0xbf0ebec4,0x3f553f6d,0xbf55bf6d,0xbf0ebec4,0xbf55bf35,0x3f0e3f35,0xbf0ebf35,0xbf55bf35,0xbf7bbf6d,0x3e483ec4,0xbe48bec4,0xbf7bbf6d,
0x0,0x3f803f80,0x0,0x3f803f80,0x0,0x3f803f80,0x0,0x3f803f80,0x0,0x3f803f80,0x0,0x3f803f80,
0x0,0x3f803f80,0x0,0x3f803f80,0xbe480000,0xbf7bbf80,0xbf7bbf80,0x3e480000,0xbf0ebec4,0xbf55bf6d,0xbf55bf6d,0x3f0e3ec4,
0xbf55bf35,0xbf0ebf35,0xbf0ebf35,0x3f553f35,0xbf7bbf6d,0xbe48bec4,0xbe48bec4,0x3f7b3f6d,0x3ec40000,0x3f6d3f80,0xbec40000,0xbf6dbf80,
0x3f6d3f35,0x3ec43f35,0xbf6dbf35,0xbec4bf35,0x3f6d3f80,0xbec40000,0xbf6dbf80,0x3ec40000,0x3ec43f35,0xbf6dbf35,0xbec4bf35,0x3f6d3f35,
0xbf0e0000,0xbf55bf80,0x3f553f80,0xbf0e0000,0xbf7bbf6d,0x3e48bec4,0xbe483ec4,0xbf7bbf6d,0xbe48bf35,0x3f7b3f35,0xbf7bbf35,0xbe48bf35,
0x3f553ec4,0x3f0e3f6d,0xbf0ebf6d,0x3f553ec4,0x3f350000,0x3f353f80,0x3f350000,0x3f353f80,0x3f353f80,0xbf350000,0x3f353f80,0xbf350000,
0xbf350000,0xbf35bf80,0xbf350000,0xbf35bf80,0xbf35bf80,0x3f350000,0xbf35bf80,0x3f350000,0xbf550000,0xbf0ebf80,0xbf0ebf80,0x3f550000,
0xbe48bf6d,0x3f7b3ec4,0x3f7b3ec4,0x3e483f6d,0x3f7b3f35,0xbe483f35,0xbe483f35,0xbf7bbf35,0xbf0e3ec4,0xbf55bf6d,0xbf55bf6d,0x3f0ebec4,
0x3f6d0000,0x3ec43f80,0xbf6d0000,0xbec4bf80,0xbec43f35,0xbf6dbf35,0x3ec4bf35,0x3f6d3f35,0xbec4bf80,0x3f6d0000,0x3ec43f80,0xbf6d0000,
0x3f6d3f35,0xbec43f35,0xbf6dbf35,0x3ec4bf35,0xbf7b0000,0xbe48bf80,0x3e483f80,0xbf7b0000,0x3f55bec4,0x3f0e3f6d,0xbf0ebf6d,0x3f55bec4,
0xbf0e3f35,0xbf55bf35,0x3f553f35,0xbf0e3f35,0x3e48bf6d,0x3f7b3ec4,0xbf7bbec4,0x3e48bf6d,0x3f800000,0x3f80,0x3f800000,0x3f80,
0xbf800000,0xbf80,0xbf800000,0xbf80,0x3f800000,0x3f80,0x3f800000,0x3f80,0xbf800000,0xbf80,0xbf800000,0xbf80,
0xbf7b0000,0x3e48bf80,0x3e48bf80,0x3f7b0000,0x3f553ec4,0xbf0e3f6d,0xbf0e3f6d,0xbf55bec4,0xbf0ebf35,0x3f55bf35,0x3f55bf35,0x3f0e3f35,
0x3e483f6d,0xbf7b3ec4,0xbf7b3ec4,0xbe48bf6d,0x3f6d0000,0xbec43f80,0xbf6d0000,0x3ec4bf80,0xbec4bf35,0x3f6dbf35,0x3ec43f35,0xbf6d3f35,
0xbec43f80,0xbf6d0000,0x3ec4bf80,0x3f6d0000,0x3f6dbf35,0x3ec43f35,0xbf6d3f35,0xbec4bf35,0xbf550000,0x3f0ebf80,0xbf0e3f80,0xbf550000,
0xbe483f6d,0xbf7b3ec4,0x3f7bbec4,0xbe483f6d,0x3f7bbf35,0x3e483f35,0xbe48bf35,0x3f7bbf35,0xbf0ebec4,0x3f55bf6d,0xbf553f6d,0xbf0ebec4,
0x3f350000,0xbf353f80,0x3f350000,0xbf353f80,0x3f35bf80,0x3f350000,0x3f35bf80,0x3f350000,0xbf350000,0x3f35bf80,0xbf350000,0x3f35bf80,
0xbf353f80,0xbf350000,0xbf353f80,0xbf350000,0xbf0e0000,0x3f55bf80,0x3f55bf80,0x3f0e0000,0xbf7b3f6d,0xbe48bec4,0xbe48bec4,0x3f7bbf6d,
0xbe483f35,0xbf7b3f35,0xbf7b3f35,0x3e48bf35,0x3f55bec4,0xbf0e3f6d,0xbf0e3f6d,0xbf553ec4,0x3ec40000,0xbf6d3f80,0xbec40000,0x3f6dbf80,
0x3f6dbf35,0xbec43f35,0xbf6d3f35,0x3ec4bf35,0x3f6dbf80,0x3ec40000,0xbf6d3f80,0xbec40000,0x3ec4bf35,0x3f6dbf35,0xbec43f35,0xbf6d3f35,
0xbe480000,0x3f7bbf80,0xbf7b3f80,0xbe480000,0xbf0e3ec4,0x3f55bf6d,0xbf553f6d,0xbf0e3ec4,0xbf553f35,0x3f0ebf35,0xbf0e3f35,0xbf553f35,
0xbf7b3f6d,0x3e48bec4,0xbe483ec4,0xbf7b3f6d,0x0,0xbf803f80,0x0,0xbf803f80,0x0,0xbf803f80,0x0,0xbf803f80,
0x0,0xbf803f80,0x0,0xbf803f80,0x0,0xbf803f80,0x0,0xbf803f80,0x3e480000,0x3f7bbf80,0x3f7bbf80,0xbe480000,
0x3f0ebec4,0x3f55bf6d,0x3f55bf6d,0xbf0e3ec4,0x3f55bf35,0x3f0ebf35,0x3f0ebf35,0xbf553f35,0x3f7bbf6d,0x3e48bec4,0x3e48bec4,0xbf7b3f6d,
0xbec40000,0xbf6d3f80,0x3ec40000,0x3f6dbf80,0xbf6d3f35,0xbec43f35,0x3f6dbf35,0x3ec4bf35,0xbf6d3f80,0x3ec40000,0x3f6dbf80,0xbec40000,
0xbec43f35,0x3f6dbf35,0x3ec4bf35,0xbf6d3f35,0x3f0e0000,0x3f55bf80,0xbf553f80,0x3f0e0000,0x3f7bbf6d,0xbe48bec4,0x3e483ec4,0x3f7bbf6d,
0x3e48bf35,0xbf7b3f35,0x3f7bbf35,0x3e48bf35,0xbf553ec4,0xbf0e3f6d,0x3f0ebf6d,0xbf553ec4,0xbf350000,0xbf353f80,0xbf350000,0xbf353f80,
0xbf353f80,0x3f350000,0xbf353f80,0x3f350000,0x3f350000,0x3f35bf80,0x3f350000,0x3f35bf80,0x3f35bf80,0xbf350000,0x3f35bf80,0xbf350000,
0x3f550000,0x3f0ebf80,0x3f0ebf80,0xbf550000,0x3e48bf6d,0xbf7b3ec4,0xbf7b3ec4,0xbe483f6d,0xbf7b3f35,0x3e483f35,0x3e483f35,0x3f7bbf35,
0x3f0e3ec4,0x3f55bf6d,0x3f55bf6d,0xbf0ebec4,0xbf6d0000,0xbec43f80,0x3f6d0000,0x3ec4bf80,0x3ec43f35,0x3f6dbf35,0xbec4bf35,0xbf6d3f35,
0x3ec4bf80,0xbf6d0000,0xbec43f80,0x3f6d0000,0xbf6d3f35,0x3ec43f35,0x3f6dbf35,0xbec4bf35,0x3f7b0000,0x3e48bf80,0xbe483f80,0x3f7b0000,
0xbf55bec4,0xbf0e3f6d,0x3f0ebf6d,0xbf55bec4,0x3f0e3f35,0x3f55bf35,0xbf553f35,0x3f0e3f35,0xbe48bf6d,0xbf7b3ec4,0x3f7bbec4,0xbe48bf6d,
0xbf800000,0x3f80,0xbf800000,0x3f80,0x3f800000,0xbf80,0x3f800000,0xbf80,0xbf800000,0x3f80,0xbf800000,0x3f80,
0x3f800000,0xbf80,0x3f800000,0xbf80,0x3f7b0000,0xbe48bf80,0xbe48bf80,0xbf7b0000,0xbf553ec4,0x3f0e3f6d,0x3f0e3f6d,0x3f55bec4,
0x3f0ebf35,0xbf55bf35,0xbf55bf35,0xbf0e3f35,0xbe483f6d,0x3f7b3ec4,0x3f7b3ec4,0x3e48bf6d,0xbf6d0000,0x3ec43f80,0x3f6d0000,0xbec4bf80,
0x3ec4bf35,0xbf6dbf35,0xbec43f35,0x3f6d3f35,0x3ec43f80,0x3f6d0000,0xbec4bf80,0xbf6d0000,0xbf6dbf35,0xbec43f35,0x3f6d3f35,0x3ec4bf35,
0x3f550000,0xbf0ebf80,0x3f0e3f80,0x3f550000,0x3e483f6d,0x3f7b3ec4,0xbf7bbec4,0x3e483f6d,0xbf7bbf35,0xbe483f35,0x3e48bf35,0xbf7bbf35,
0x3f0ebec4,0xbf55bf6d,0x3f553f6d,0x3f0ebec4,0xbf350000,0x3f353f80,0xbf350000,0x3f353f80,0xbf35bf80,0xbf350000,0xbf35bf80,0xbf350000,
0x3f350000,0xbf35bf80,0x3f350000,0xbf35bf80,0x3f353f80,0x3f350000,0x3f353f80,0x3f350000,0x3f0e0000,0xbf55bf80,0xbf55bf80,0xbf0e0000,
0x3f7b3f6d,0x3e48bec4,0x3e48bec4,0xbf7bbf6d,0x3e483f35,0x3f7b3f35,0x3f7b3f35,0xbe48bf35,0xbf55bec4,0x3f0e3f6d,0x3f0e3f6d,0x3f553ec4,
0xbec40000,0x3f6d3f80,0x3ec40000,0xbf6dbf80,0xbf6dbf35,0x3ec43f35,0x3f6d3f35,0xbec4bf35,0xbf6dbf80,0xbec40000,0x3f6d3f80,0x3ec40000,
0xbec4bf35,0xbf6dbf35,0x3ec43f35,0x3f6d3f35,0x3e480000,0xbf7bbf80,0x3f7b3f80,0x3e480000,0x3f0e3ec4,0xbf55bf6d,0x3f553f6d,0x3f0e3ec4,
0x3f553f35,0xbf0ebf35,0x3f0e3f35,0x3f553f35,0x3f7b3f6d,0xbe48bec4,0x3e483ec4,0x3f7b3f6d,
};
__device__ __align__(128) const uint32_t T_a4[2048] = {
0x3a003a00,0x0,0x3a003a00,0x0,0x3a003a00,0x0,0x3a003a00,0x0,0x3a003a00,0x0,0x3a003a00,0x0,
0x3a003a00,0x0,0x3a003a00,0x0,0x39fb3a00,0x38c80000,0xb8c80000,0x39fb3a00,0x39d539ed,0x398e3944,0xb98eb944,0x39d539ed,
0x398e39b5,0x39d539b5,0xb9d5b9b5,0x398e39b5,0x38c83944,0x39fb39ed,0xb9fbb9ed,0x38c83944,0x39ed3a00,0x39440000,0xb9edba00,0xb9440000,
0x394439b5,0x39ed39b5,0xb944b9b5,0xb9edb9b5,0xb9440000,0x39ed3a00,0x39440000,0xb9edba00,0xb9edb9b5,0x394439b5,0x39ed39b5,0xb944b9b5,
0x39d53a00,0x398e0000,0x398e0000,0xb9d5ba00,0xb8c83944,0x39fb39ed,0x39fb39ed,0x38c8b944,0xb9fbb9b5,0x38c839b5,0x38c839b5,0x39fb39b5,
0xb98eb9ed,0xb9d5b944,0xb9d5b944,0x398e39ed,0x39b53a00,0x39b50000,0x39b53a00,0x39b50000,0xb9b50000,0x39b53a00,0xb9b50000,0x39b53a00,
0xb9b5ba00,0xb9b50000,0xb9b5ba00,0xb9b50000,0x39b50000,0xb9b5ba00,0x39b50000,0xb9b5ba00,0x398e3a00,0x39d50000,0xb9d50000,0x398e3a00,
0xb9fbb944,0x38c839ed,0xb8c8b9ed,0xb9fbb944,0x38c8b9b5,0xb9fbb9b5,0x39fb39b5,0x38c8b9b5,0x39d539ed,0x398eb944,0xb98e3944,0x39d539ed,
0x39443a00,0x39ed0000,0xb944ba00,0xb9ed0000,0xb9edb9b5,0xb94439b5,0x39ed39b5,0x3944b9b5,0x39ed0000,0xb944ba00,0xb9ed0000,0x39443a00,
0xb94439b5,0x39ed39b5,0x3944b9b5,0xb9edb9b5,0x38c83a00,0x39fb0000,0x39fb0000,0xb8c8ba00,0xb98eb9ed,0xb9d53944,0xb9d53944,0x398e39ed,
0x39d539b5,0x398eb9b5,0x398eb9b5,0xb9d5b9b5,0xb9fbb944,0xb8c839ed,0xb8c839ed,0x39fb3944,0x3a00,0x3a000000,0x3a00,0x3a000000,
0xba00,0xba000000,0xba00,0xba000000,0x3a00,0x3a000000,0x3a00,0x3a000000,0xba00,0xba000000,0xba00,0xba000000,
0xb8c83a00,0x39fb0000,0xb9fb0000,0xb8c83a00,0x398eb9ed,0xb9d5b944,0x39d53944,0x398eb9ed,0xb9d539b5,0x398e39b5,0xb98eb9b5,0xb9d539b5,
0x39fbb944,0xb8c8b9ed,0x38c839ed,0x39fbb944,0xb9443a00,0x39ed0000,0x3944ba00,0xb9ed0000,0x39edb9b5,0xb944b9b5,0xb9ed39b5,0x394439b5,
0xb9ed0000,0xb9443a00,0x39ed0000,0x3944ba00,0x394439b5,0x39edb9b5,0xb944b9b5,0xb9ed39b5,0xb98e3a00,0x39d50000,0x39d50000,0x398eba00,
0x39fbb944,0x38c8b9ed,0x38c8b9ed,0xb9fb3944,0xb8c8b9b5,0xb9fb39b5,0xb9fb39b5,0x38c839b5,0xb9d539ed,0x398e3944,0x398e3944,0x39d5b9ed,
0xb9b53a00,0x39b50000,0xb9b53a00,0x39b50000,0x39b50000,0x39b5ba00,0x39b50000,0x39b5ba00,0x39b5ba00,0xb9b50000,0x39b5ba00,0xb9b50000,
0xb9b50000,0xb9b53a00,0xb9b50000,0xb9b53a00,0xb9d53a00,0x398e0000,0xb98e0000,0xb9d53a00,0x38c83944,0x39fbb9ed,0xb9fb39ed,0x38c83944,
0x39fbb9b5,0x38c8b9b5,0xb8c839b5,0x39fbb9b5,0x398eb9ed,0xb9d53944,0x39d5b944,0x398eb9ed,0xb9ed3a00,0x39440000,0x39edba00,0xb9440000,
0xb94439b5,0x39edb9b5,0x3944b9b5,0xb9ed39b5,0x39440000,0x39edba00,0xb9440000,0xb9ed3a00,0x39edb9b5,0x3944b9b5,0xb9ed39b5,0xb94439b5,
0xb9fb3a00,0x38c80000,0x38c80000,0x39fbba00,0xb9d539ed,0x398eb944,0x398eb944,0x39d5b9ed,0xb98e39b5,0x39d5b9b5,0x39d5b9b5,0x398eb9b5,
0xb8c83944,0x39fbb9ed,0x39fbb9ed,0x38c8b944,0xba003a00,0x0,0xba003a00,0x0,0xba003a00,0x0,0xba003a00,0x0,
0xba003a00,0x0,0xba003a00,0x0,0xba003a00,0x0,0xba003a00,0x0,0xb9fb3a00,0xb8c80000,0x38c80000,0xb9fb3a00,
0xb9d539ed,0xb98e3944,0x398eb944,0xb9d539ed,0xb98e39b5,0xb9d539b5,0x39d5b9b5,0xb98e39b5,0xb8c83944,0xb9fb39ed,0x39fbb9ed,0xb8c83944,
0xb9ed3a00,0xb9440000,0x39edba00,0x39440000,0xb94439b5,0xb9ed39b5,0x3944b9b5,0x39edb9b5,0x39440000,0xb9ed3a00,0xb9440000,0x39edba00,
0x39edb9b5,0xb94439b5,0xb9ed39b5,0x3944b9b5,0xb9d53a00,0xb98e0000,0xb98e0000,0x39d5ba00,0x38c83944,0xb9fb39ed,0xb9fb39ed,0xb8c8b944,
0x39fbb9b5,0xb8c839b5,0xb8c839b5,0xb9fb39b5,0x398eb9ed,0x39d5b944,0x39d5b944,0xb98e39ed,0xb9b53a00,0xb9b50000,0xb9b53a00,0xb9b50000,
0x39b50000,0xb9b53a00,0x39b50000,0xb9b53a00,0x39b5ba00,0x39b50000,0x39b5ba00,0x39b50000,0xb9b50000,0x39b5ba00,0xb9b50000,0x39b5ba00,
0xb98e3a00,0xb9d50000,0x39d50000,0xb98e3a00,0x39fbb944,0xb8c839ed,0x38c8b9ed,0x39fbb944,0xb8c8b9b5,0x39fbb9b5,0xb9fb39b5,0xb8c8b9b5,
0xb9d539ed,0xb98eb944,0x398e3944,0xb9d539ed,0xb9443a00,0xb9ed0000,0x3944ba00,0x39ed0000,0x39edb9b5,0x394439b5,0xb9ed39b5,0xb944b9b5,
0xb9ed0000,0x3944ba00,0x39ed0000,0xb9443a00,0x394439b5,0xb9ed39b5,0xb944b9b5,0x39edb9b5,0xb8c83a00,0xb9fb0000,0xb9fb0000,0x38c8ba00,
0x398eb9ed,0x39d53944,0x39d53944,0xb98e39ed,0xb9d539b5,0xb98eb9b5,0xb98eb9b5,0x39d5b9b5,0x39fbb944,0x38c839ed,0x38c839ed,0xb9fb3944,
0x3a00,0xba000000,0x3a00,0xba000000,0xba00,0x3a000000,0xba00,0x3a000000,0x3a00,0xba000000,0x3a00,0xba000000,
0xba00,0x3a000000,0xba00,0x3a000000,0x38c83a00,0xb9fb0000,0x39fb0000,0x38c83a00,0xb98eb9ed,0x39d5b944,0xb9d53944,0xb98eb9ed,
0x39d539b5,0xb98e39b5,0x398eb9b5,0x39d539b5,0xb9fbb944,0x38c8b9ed,0xb8c839ed,0xb9fbb944,0x39443a00,0xb9ed0000,0xb944ba00,0x39ed0000,
0xb9edb9b5,0x3944b9b5,0x39ed39b5,0xb94439b5,0x39ed0000,0x39443a00,0xb9ed0000,0xb944ba00,0xb94439b5,0xb9edb9b5,0x3944b9b5,0x39ed39b5,
0x398e3a00,0xb9d50000,0xb9d50000,0xb98eba00,0xb9fbb944,0xb8c8b9ed,0xb8c8b9ed,0x39fb3944,0x38c8b9b5,0x39fb39b5,0x39fb39b5,0xb8c839b5,
0x39d539ed,0xb98e3944,0xb98e3944,0xb9d5b9ed,0x39b53a00,0xb9b50000,0x39b53a00,0xb9b50000,0xb9b50000,0xb9b5ba00,0xb9b50000,0xb9b5ba00,
0xb9b5ba00,0x39b50000,0xb9b5ba00,0x39b50000,0x39b50000,0x39b53a00,0x39b50000,0x39b53a00,0x39d53a00,0xb98e0000,0x398e0000,0x39d53a00,
0xb8c83944,0xb9fbb9ed,0x39fb39ed,0xb8c83944,0xb9fbb9b5,0xb8c8b9b5,0x38c839b5,0xb9fbb9b5,0xb98eb9ed,0x39d53944,0xb9d5b944,0xb98eb9ed,
0x39ed3a00,0xb9440000,0xb9edba00,0x39440000,0x394439b5,0xb9edb9b5,0xb944b9b5,0x39ed39b5,0xb9440000,0xb9edba00,0x39440000,0x39ed3a00,
0xb9edb9b5,0xb944b9b5,0x39ed39b5,0x394439b5,0x39fb3a00,0xb8c80000,0xb8c80000,0xb9fbba00,0x39d539ed,0xb98eb944,0xb98eb944,0xb9d5b9ed,
0x398e39b5,0xb9d5b9b5,0xb9d5b9b5,0xb98eb9b5,0x38c83944,0xb9fbb9ed,0xb9fbb9ed,0xb8c8b944,0x3a003a00,0x0,0x3a003a00,0x0,
0x3a003a00,0x0,0x3a003a00,0x0,0x3a003a00,0x0,0x3a003a00,0x0,0x3a003a00,0x0,0x3a003a00,0x0,
0xb9fbba00,0xb8c80000,0x38c80000,0xb9fbba00,0xb9d5b9ed,0xb98eb944,0x398e3944,0xb9d5b9ed,0xb98eb9b5,0xb9d5b9b5,0x39d539b5,0xb98eb9b5,
0xb8c8b944,0xb9fbb9ed,0x39fb39ed,0xb8c8b944,0x39ed3a00,0x39440000,0xb9edba00,0xb9440000,0x394439b5,0x39ed39b5,0xb944b9b5,0xb9edb9b5,
0xb9440000,0x39ed3a00,0x39440000,0xb9edba00,0xb9edb9b5,0x394439b5,0x39ed39b5,0xb944b9b5,0xb9d5ba00,0xb98e0000,0xb98e0000,0x39d53a00,
0x38c8b944,0xb9fbb9ed,0xb9fbb9ed,0xb8c83944,0x39fb39b5,0xb8c8b9b5,0xb8c8b9b5,0xb9fbb9b5,0x398e39ed,0x39d53944,0x39d53944,0xb98eb9ed,
0x39b53a00,0x39b50000,0x39b53a00,0x39b50000,0xb9b50000,0x39b53a00,0xb9b50000,0x39b53a00,0xb9b5ba00,0xb9b50000,0xb9b5ba00,0xb9b50000,
0x39b50000,0xb9b5ba00,0x39b50000,0xb9b5ba00,0xb98eba00,0xb9d50000,0x39d50000,0xb98eba00,0x39fb3944,0xb8c8b9ed,0x38c839ed,0x39fb3944,
0xb8c839b5,0x39fb39b5,0xb9fbb9b5,0xb8c839b5,0xb9d5b9ed,0xb98e3944,0x398eb944,0xb9d5b9ed,0x39443a00,0x39ed0000,0xb944ba00,0xb9ed0000,
0xb9edb9b5,0xb94439b5,0x39ed39b5,0x3944b9b5,0x39ed0000,0xb944ba00,0xb9ed0000,0x39443a00,0xb94439b5,0x39ed39b5,0x3944b9b5,0xb9edb9b5,
0xb8c8ba00,0xb9fb0000,0xb9fb0000,0x38c83a00,0x398e39ed,0x39d5b944,0x39d5b944,0xb98eb9ed,0xb9d5b9b5,0xb98e39b5,0xb98e39b5,0x39d539b5,
0x39fb3944,0x38c8b9ed,0x38c8b9ed,0xb9fbb944,0x3a00,0x3a000000,0x3a00,0x3a000000,0xba00,0xba000000,0xba00,0xba000000,
0x3a00,0x3a000000,0x3a00,0x3a000000,0xba00,0xba000000,0xba00,0xba000000,0x38c8ba00,0xb9fb0000,0x39fb0000,0x38c8ba00,
0xb98e39ed,0x39d53944,0xb9d5b944,0xb98e39ed,0x39d5b9b5,0xb98eb9b5,0x398e39b5,0x39d5b9b5,0xb9fb3944,0x38c839ed,0xb8c8b9ed,0xb9fb3944,
0xb9443a00,0x39ed0000,0x3944ba00,0xb9ed0000,0x39edb9b5,0xb944b9b5,0xb9ed39b5,0x394439b5,0xb9ed0000,0xb9443a00,0x39ed0000,0x3944ba00,
0x394439b5,0x39edb9b5,0xb944b9b5,0xb9ed39b5,0x398eba00,0xb9d50000,0xb9d50000,0xb98e3a00,0xb9fb3944,0xb8c839ed,0xb8c839ed,0x39fbb944,
0x38c839b5,0x39fbb9b5,0x39fbb9b5,0xb8c8b9b5,0x39d5b9ed,0xb98eb944,0xb98eb944,0xb9d539ed,0xb9b53a00,0x39b50000,0xb9b53a00,0x39b50000,
0x39b50000,0x39b5ba00,0x39b50000,0x39b5ba00,0x39b5ba00,0xb9b50000,0x39b5ba00,0xb9b50000,0xb9b50000,0xb9b53a00,0xb9b50000,0xb9b53a00,
0x39d5ba00,0xb98e0000,0x398e0000,0x39d5ba00,0xb8c8b944,0xb9fb39ed,0x39fbb9ed,0xb8c8b944,0xb9fb39b5,0xb8c839b5,0x38c8b9b5,0xb9fb39b5,
0xb98e39ed,0x39d5b944,0xb9d53944,0xb98e39ed,0xb9ed3a00,0x39440000,0x39edba00,0xb9440000,0xb94439b5,0x39edb9b5,0x3944b9b5,0xb9ed39b5,
0x39440000,0x39edba00,0xb9440000,0xb9ed3a00,0x39edb9b5,0x3944b9b5,0xb9ed39b5,0xb94439b5,0x39fbba00,0xb8c80000,0xb8c80000,0xb9fb3a00,
0x39d5b9ed,0xb98e3944,0xb98e3944,0xb9d539ed,0x398eb9b5,0xb9d539b5,0xb9d539b5,0xb98e39b5,0x38c8b944,0xb9fb39ed,0xb9fb39ed,0xb8c83944,
0xba003a00,0x0,0xba003a00,0x0,0xba003a00,0x0,0xba003a00,0x0,0xba003a00,0x0,0xba003a00,0x0,
0xba003a00,0x0,0xba003a00,0x0,0x39fbba00,0x38c80000,0xb8c80000,0x39fbba00,0x39d5b9ed,0x398eb944,0xb98e3944,0x39d5b9ed,
0x398eb9b5,0x39d5b9b5,0xb9d539b5,0x398eb9b5,0x38c8b944,0x39fbb9ed,0xb9fb39ed,0x38c8b944,0xb9ed3a00,0xb9440000,0x39edba00,0x39440000,
0xb94439b5,0xb9ed39b5,0x3944b9b5,0x39edb9b5,0x39440000,0xb9ed3a00,0xb9440000,0x39edba00,0x39edb9b5,0xb94439b5,0xb9ed39b5,0x3944b9b5,
0x39d5ba00,0x398e0000,0x398e0000,0xb9d53a00,0xb8c8b944,0x39fbb9ed,0x39fbb9ed,0x38c83944,0xb9fb39b5,0x38c8b9b5,0x38c8b9b5,0x39fbb9b5,
0xb98e39ed,0xb9d53944,0xb9d53944,0x398eb9ed,0xb9b53a00,0xb9b50000,0xb9b53a00,0xb9b50000,0x39b50000,0xb9b53a00,0x39b50000,0xb9b53a00,
0x39b5ba00,0x39b50000,0x39b5ba00,0x39b50000,0xb9b50000,0x39b5ba00,0xb9b50000,0x39b5ba00,0x398eba00,0x39d50000,0xb9d50000,0x398eba00,
0xb9fb3944,0x38c8b9ed,0xb8c839ed,0xb9fb3944,0x38c839b5,0xb9fb39b5,0x39fbb9b5,0x38c839b5,0x39d5b9ed,0x398e3944,0xb98eb944,0x39d5b9ed,
0xb9443a00,0xb9ed0000,0x3944ba00,0x39ed0000,0x39edb9b5,0x394439b5,0xb9ed39b5,0xb944b9b5,0xb9ed0000,0x3944ba00,0x39ed0000,0xb9443a00,
0x394439b5,0xb9ed39b5,0xb944b9b5,0x39edb9b5,0x38c8ba00,0x39fb0000,0x39fb0000,0xb8c83a00,0xb98e39ed,0xb9d5b944,0xb9d5b944,0x398eb9ed,
0x39d5b9b5,0x398e39b5,0x398e39b5,0xb9d539b5,0xb9fb3944,0xb8c8b9ed,0xb8c8b9ed,0x39fbb944,0x3a00,0xba000000,0x3a00,0xba000000,
0xba00,0x3a000000,0xba00,0x3a000000,0x3a00,0xba000000,0x3a00,0xba000000,0xba00,0x3a000000,0xba00,0x3a000000,
0xb8c8ba00,0x39fb0000,0xb9fb0000,0xb8c8ba00,0x398e39ed,0xb9d53944,0x39d5b944,0x398e39ed,0xb9d5b9b5,0x398eb9b5,0xb98e39b5,0xb9d5b9b5,
0x39fb3944,0xb8c839ed,0x38c8b9ed,0x39fb3944,0x39443a00,0xb9ed0000,0xb944ba00,0x39ed0000,0xb9edb9b5,0x3944b9b5,0x39ed39b5,0xb94439b5,
0x39ed0000,0x39443a00,0xb9ed0000,0xb944ba00,0xb94439b5,0xb9edb9b5,0x3944b9b5,0x39ed39b5,0xb98eba00,0x39d50000,0x39d50000,0x398e3a00,
0x39fb3944,0x38c839ed,0x38c839ed,0xb9fbb944,0xb8c839b5,0xb9fbb9b5,0xb9fbb9b5,0x38c8b9b5,0xb9d5b9ed,0x398eb944,0x398eb944,0x39d539ed,
0x39b53a00,0xb9b50000,0x39b53a00,0xb9b50000,0xb9b50000,0xb9b5ba00,0xb9b50000,0xb9b5ba00,0xb9b5ba00,0x39b50000,0xb9b5ba00,0x39b50000,
0x39b50000,0x39b53a00,0x39b50000,0x39b53a00,0xb9d5ba00,0x398e0000,0xb98e0000,0xb9d5ba00,0x38c8b944,0x39fb39ed,0xb9fbb9ed,0x38c8b944,
0x39fb39b5,0x38c839b5,0xb8c8b9b5,0x39fb39b5,0x398e39ed,0xb9d5b944,0x39d53944,0x398e39ed,0x39ed3a00,0xb9440000,0xb9edba00,0x39440000,
0x394439b5,0xb9edb9b5,0xb944b9b5,0x39ed39b5,0xb9440000,0xb9edba00,0x39440000,0x39ed3a00,0xb9edb9b5,0xb944b9b5,0x39ed39b5,0x394439b5,
0xb9fbba00,0x38c80000,0x38c80000,0x39fb3a00,0xb9d5b9ed,0x398e3944,0x398e3944,0x39d539ed,0xb98eb9b5,0x39d539b5,0x39d539b5,0x398e39b5,
0xb8c8b944,0x39fb39ed,0x39fb39ed,0x38c83944,0x0,0x3a003a00,0x0,0x3a003a00,0x0,0x3a003a00,0x0,0x3a003a00,
0x0,0x3a003a00,0x0,0x3a003a00,0x0,0x3a003a00,0x0,0x3a003a00,0xb8c80000,0x39fb3a00,0xb9fbba00,0xb8c80000,
0xb98eb944,0x39d539ed,0xb9d5b9ed,0xb98eb944,0xb9d5b9b5,0x398e39b5,0xb98eb9b5,0xb9d5b9b5,0xb9fbb9ed,0x38c83944,0xb8c8b944,0xb9fbb9ed,
0xb9440000,0x39ed3a00,0x39440000,0xb9edba00,0xb9edb9b5,0x394439b5,0x39ed39b5,0xb944b9b5,0xb9edba00,0xb9440000,0x39ed3a00,0x39440000,
0xb944b9b5,0xb9edb9b5,0x394439b5,0x39ed39b5,0xb98e0000,0x39d53a00,0x39d53a00,0x398e0000,0xb9fbb9ed,0xb8c83944,0xb8c83944,0x39fb39ed,
0xb8c8b9b5,0xb9fbb9b5,0xb9fbb9b5,0x38c839b5,0x39d53944,0xb98eb9ed,0xb98eb9ed,0xb9d5b944,0xb9b50000,0x39b53a00,0xb9b50000,0x39b53a00,
0xb9b5ba00,0xb9b50000,0xb9b5ba00,0xb9b50000,0x39b50000,0xb9b5ba00,0x39b50000,0xb9b5ba00,0x39b53a00,0x39b50000,0x39b53a00,0x39b50000,
0xb9d50000,0x398e3a00,0xb98eba00,0xb9d50000,0xb8c8b9ed,0xb9fbb944,0x39fb3944,0xb8c8b9ed,0x39fb39b5,0x38c8b9b5,0xb8c839b5,0x39fb39b5,
0xb98e3944,0x39d539ed,0xb9d5b9ed,0xb98e3944,0xb9ed0000,0x39443a00,0x39ed0000,0xb944ba00,0x3944b9b5,0xb9edb9b5,0xb94439b5,0x39ed39b5,
0x39443a00,0x39ed0000,0xb944ba00,0xb9ed0000,0xb9edb9b5,0xb94439b5,0x39ed39b5,0x3944b9b5,0xb9fb0000,0x38c83a00,0x38c83a00,0x39fb0000,
0x39d5b944,0xb98eb9ed,0xb98eb9ed,0xb9d53944,0xb98e39b5,0x39d539b5,0x39d539b5,0x398eb9b5,0x38c8b9ed,0xb9fbb944,0xb9fbb944,0xb8c839ed,
0xba000000,0x3a00,0xba000000,0x3a00,0x3a000000,0xba00,0x3a000000,0xba00,0xba000000,0x3a00,0xba000000,0x3a00,
0x3a000000,0xba00,0x3a000000,0xba00,0xb9fb0000,0xb8c83a00,0x38c8ba00,0xb9fb0000,0x39d53944,0x398eb9ed,0xb98e39ed,0x39d53944,
0xb98eb9b5,0xb9d539b5,0x39d5b9b5,0xb98eb9b5,0x38c839ed,0x39fbb944,0xb9fb3944,0x38c839ed,0xb9ed0000,0xb9443a00,0x39ed0000,0x3944ba00,
0x394439b5,0x39edb9b5,0xb944b9b5,0xb9ed39b5,0x3944ba00,0xb9ed0000,0xb9443a00,0x39ed0000,0xb9ed39b5,0x394439b5,0x39edb9b5,0xb944b9b5,
0xb9d50000,0xb98e3a00,0xb98e3a00,0x39d50000,0xb8c839ed,0x39fbb944,0x39fbb944,0x38c8b9ed,0x39fbb9b5,0xb8c8b9b5,0xb8c8b9b5,0xb9fb39b5,
0xb98eb944,0xb9d539ed,0xb9d539ed,0x398e3944,0xb9b50000,0xb9b53a00,0xb9b50000,0xb9b53a00,0xb9b53a00,0x39b50000,0xb9b53a00,0x39b50000,
0x39b50000,0x39b5ba00,0x39b50000,0x39b5ba00,0x39b5ba00,0xb9b50000,0x39b5ba00,0xb9b50000,0xb98e0000,0xb9d53a00,0x39d5ba00,0xb98e0000,
0xb9fb39ed,0x38c83944,0xb8c8b944,0xb9fb39ed,0xb8c839b5,0x39fbb9b5,0xb9fb39b5,0xb8c839b5,0x39d5b944,0x398eb9ed,0xb98e39ed,0x39d5b944,
0xb9440000,0xb9ed3a00,0x39440000,0x39edba00,0xb9ed39b5,0xb94439b5,0x39edb9b5,0x3944b9b5,0xb9ed3a00,0x39440000,0x39edba00,0xb9440000,
0xb94439b5,0x39edb9b5,0x3944b9b5,0xb9ed39b5,0xb8c80000,0xb9fb3a00,0xb9fb3a00,0x38c80000,0xb98e3944,0xb9d539ed,0xb9d539ed,0x398eb944,
0xb9d539b5,0xb98e39b5,0xb98e39b5,0x39d5b9b5,0xb9fb39ed,0xb8c83944,0xb8c83944,0x39fbb9ed,0x0,0xba003a00,0x0,0xba003a00,
0x0,0xba003a00,0x0,0xba003a00,0x0,0xba003a00,0x0,0xba003a00,0x0,0xba003a00,0x0,0xba003a00,
0x38c80000,0xb9fb3a00,0x39fbba00,0x38c80000,0x398eb944,0xb9d539ed,0x39d5b9ed,0x398eb944,0x39d5b9b5,0xb98e39b5,0x398eb9b5,0x39d5b9b5,
0x39fbb9ed,0xb8c83944,0x38c8b944,0x39fbb9ed,0x39440000,0xb9ed3a00,0xb9440000,0x39edba00,0x39edb9b5,0xb94439b5,0xb9ed39b5,0x3944b9b5,
0x39edba00,0x39440000,0xb9ed3a00,0xb9440000,0x3944b9b5,0x39edb9b5,0xb94439b5,0xb9ed39b5,0x398e0000,0xb9d53a00,0xb9d53a00,0xb98e0000,
0x39fbb9ed,0x38c83944,0x38c83944,0xb9fb39ed,0x38c8b9b5,0x39fbb9b5,0x39fbb9b5,0xb8c839b5,0xb9d53944,0x398eb9ed,0x398eb9ed,0x39d5b944,
0x39b50000,0xb9b53a00,0x39b50000,0xb9b53a00,0x39b5ba00,0x39b50000,0x39b5ba00,0x39b50000,0xb9b50000,0x39b5ba00,0xb9b50000,0x39b5ba00,
0xb9b53a00,0xb9b50000,0xb9b53a00,0xb9b50000,0x39d50000,0xb98e3a00,0x398eba00,0x39d50000,0x38c8b9ed,0x39fbb944,0xb9fb3944,0x38c8b9ed,
0xb9fb39b5,0xb8c8b9b5,0x38c839b5,0xb9fb39b5,0x398e3944,0xb9d539ed,0x39d5b9ed,0x398e3944,0x39ed0000,0xb9443a00,0xb9ed0000,0x3944ba00,
0xb944b9b5,0x39edb9b5,0x394439b5,0xb9ed39b5,0xb9443a00,0xb9ed0000,0x3944ba00,0x39ed0000,0x39edb9b5,0x394439b5,0xb9ed39b5,0xb944b9b5,
0x39fb0000,0xb8c83a00,0xb8c83a00,0xb9fb0000,0xb9d5b944,0x398eb9ed,0x398eb9ed,0x39d53944,0x398e39b5,0xb9d539b5,0xb9d539b5,0xb98eb9b5,
0xb8c8b9ed,0x39fbb944,0x39fbb944,0x38c839ed,0x3a000000,0x3a00,0x3a000000,0x3a00,0xba000000,0xba00,0xba000000,0xba00,
0x3a000000,0x3a00,0x3a000000,0x3a00,0xba000000,0xba00,0xba000000,0xba00,0x39fb0000,0x38c83a00,0xb8c8ba00,0x39fb0000,
0xb9d53944,0xb98eb9ed,0x398e39ed,0xb9d53944,0x398eb9b5,0x39d539b5,0xb9d5b9b5,0x398eb9b5,0xb8c839ed,0xb9fbb944,0x39fb3944,0xb8c839ed,
0x39ed0000,0x39443a00,0xb9ed0000,0xb944ba00,0xb94439b5,0xb9edb9b5,0x3944b9b5,0x39ed39b5,0xb944ba00,0x39ed0000,0x39443a00,0xb9ed0000,
0x39ed39b5,0xb94439b5,0xb9edb9b5,0x3944b9b5,0x39d50000,0x398e3a00,0x398e3a00,0xb9d50000,0x38c839ed,0xb9fbb944,0xb9fbb944,0xb8c8b9ed,
0xb9fbb9b5,0x38c8b9b5,0x38c8b9b5,0x39fb39b5,0x398eb944,0x39d539ed,0x39d539ed,0xb98e3944,0x39b50000,0x39b53a00,0x39b50000,0x39b53a00,
0x39b53a00,0xb9b50000,0x39b53a00,0xb9b50000,0xb9b50000,0xb9b5ba00,0xb9b50000,0xb9b5ba00,0xb9b5ba00,0x39b50000,0xb9b5ba00,0x39b50000,
0x398e0000,0x39d53a00,0xb9d5ba00,0x398e0000,0x39fb39ed,0xb8c83944,0x38c8b944,0x39fb39ed,0x38c839b5,0xb9fbb9b5,0x39fb39b5,0x38c839b5,
0xb9d5b944,0xb98eb9ed,0x398e39ed,0xb9d5b944,0x39440000,0x39ed3a00,0xb9440000,0xb9edba00,0x39ed39b5,0x394439b5,0xb9edb9b5,0xb944b9b5,
0x39ed3a00,0xb9440000,0xb9edba00,0x39440000,0x394439b5,0xb9edb9b5,0xb944b9b5,0x39ed39b5,0x38c80000,0x39fb3a00,0x39fb3a00,0xb8c80000,
0x398e3944,0x39d539ed,0x39d539ed,0xb98eb944,0x39d539b5,0x398e39b5,0x398e39b5,0xb9d5b9b5,0x39fb39ed,0x38c83944,0x38c83944,0xb9fbb9ed,
0x0,0x3a003a00,0x0,0x3a003a00,0x0,0x3a003a00,0x0,0x3a003a00,0x0,0x3a003a00,0x0,0x3a003a00,
0x0,0x3a003a00,0x0,0x3a003a00,0x38c80000,0xb9fbba00,0x39fb3a00,0x38c80000,0x398e3944,0xb9d5b9ed,0x39d539ed,0x398e3944,
0x39d539b5,0xb98eb9b5,0x398e39b5,0x39d539b5,0x39fb39ed,0xb8c8b944,0x38c83944,0x39fb39ed,0xb9440000,0x39ed3a00,0x39440000,0xb9edba00,
0xb9edb9b5,0x394439b5,0x39ed39b5,0xb944b9b5,0xb9edba00,0xb9440000,0x39ed3a00,0x39440000,0xb944b9b5,0xb9edb9b5,0x394439b5,0x39ed39b5,
0x398e0000,0xb9d5ba00,0xb9d5ba00,0xb98e0000,0x39fb39ed,0x38c8b944,0x38c8b944,0xb9fbb9ed,0x38c839b5,0x39fb39b5,0x39fb39b5,0xb8c8b9b5,
0xb9d5b944,0x398e39ed,0x398e39ed,0x39d53944,0xb9b50000,0x39b53a00,0xb9b50000,0x39b53a00,0xb9b5ba00,0xb9b50000,0xb9b5ba00,0xb9b50000,
0x39b50000,0xb9b5ba00,0x39b50000,0xb9b5ba00,0x39b53a00,0x39b50000,0x39b53a00,0x39b50000,0x39d50000,0xb98eba00,0x398e3a00,0x39d50000,
0x38c839ed,0x39fb3944,0xb9fbb944,0x38c839ed,0xb9fbb9b5,0xb8c839b5,0x38c8b9b5,0xb9fbb9b5,0x398eb944,0xb9d5b9ed,0x39d539ed,0x398eb944,
0xb9ed0000,0x39443a00,0x39ed0000,0xb944ba00,0x3944b9b5,0xb9edb9b5,0xb94439b5,0x39ed39b5,0x39443a00,0x39ed0000,0xb944ba00,0xb9ed0000,
0xb9edb9b5,0xb94439b5,0x39ed39b5,0x3944b9b5,0x39fb0000,0xb8c8ba00,0xb8c8ba00,0xb9fb0000,0xb9d53944,0x398e39ed,0x398e39ed,0x39d5b944,
0x398eb9b5,0xb9d5b9b5,0xb9d5b9b5,0xb98e39b5,0xb8c839ed,0x39fb3944,0x39fb3944,0x38c8b9ed,0xba000000,0x3a00,0xba000000,0x3a00,
0x3a000000,0xba00,0x3a000000,0xba00,0xba000000,0x3a00,0xba000000,0x3a00,0x3a000000,0xba00,0x3a000000,0xba00,
0x39fb0000,0x38c8ba00,0xb8c83a00,0x39fb0000,0xb9d5b944,0xb98e39ed,0x398eb9ed,0xb9d5b944,0x398e39b5,0x39d5b9b5,0xb9d539b5,0x398e39b5,
0xb8c8b9ed,0xb9fb3944,0x39fbb944,0xb8c8b9ed,0xb9ed0000,0xb9443a00,0x39ed0000,0x3944ba00,0x394439b5,0x39edb9b5,0xb944b9b5,0xb9ed39b5,
0x3944ba00,0xb9ed0000,0xb9443a00,0x39ed0000,0xb9ed39b5,0x394439b5,0x39edb9b5,0xb944b9b5,0x39d50000,0x398eba00,0x398eba00,0xb9d50000,
0x38c8b9ed,0xb9fb3944,0xb9fb3944,0xb8c839ed,0xb9fb39b5,0x38c839b5,0x38c839b5,0x39fbb9b5,0x398e3944,0x39d5b9ed,0x39d5b9ed,0xb98eb944,
0xb9b50000,0xb9b53a00,0xb9b50000,0xb9b53a00,0xb9b53a00,0x39b50000,0xb9b53a00,0x39b50000,0x39b50000,0x39b5ba00,0x39b50000,0x39b5ba00,
0x39b5ba00,0xb9b50000,0x39b5ba00,0xb9b50000,0x398e0000,0x39d5ba00,0xb9d53a00,0x398e0000,0x39fbb9ed,0xb8c8b944,0x38c83944,0x39fbb9ed,
0x38c8b9b5,0xb9fb39b5,0x39fbb9b5,0x38c8b9b5,0xb9d53944,0xb98e39ed,0x398eb9ed,0xb9d53944,0xb9440000,0xb9ed3a00,0x39440000,0x39edba00,
0xb9ed39b5,0xb94439b5,0x39edb9b5,0x3944b9b5,0xb9ed3a00,0x39440000,0x39edba00,0xb9440000,0xb94439b5,0x39edb9b5,0x3944b9b5,0xb9ed39b5,
0x38c80000,0x39fbba00,0x39fbba00,0xb8c80000,0x398eb944,0x39d5b9ed,0x39d5b9ed,0xb98e3944,0x39d5b9b5,0x398eb9b5,0x398eb9b5,0xb9d539b5,
0x39fbb9ed,0x38c8b944,0x38c8b944,0xb9fb39ed,0x0,0xba003a00,0x0,0xba003a00,0x0,0xba003a00,0x0,0xba003a00,
0x0,0xba003a00,0x0,0xba003a00,0x0,0xba003a00,0x0,0xba003a00,0xb8c80000,0x39fbba00,0xb9fb3a00,0xb8c80000,
0xb98e3944,0x39d5b9ed,0xb9d539ed,0xb98e3944,0xb9d539b5,0x398eb9b5,0xb98e39b5,0xb9d539b5,0xb9fb39ed,0x38c8b944,0xb8c83944,0xb9fb39ed,
0x39440000,0xb9ed3a00,0xb9440000,0x39edba00,0x39edb9b5,0xb94439b5,0xb9ed39b5,0x3944b9b5,0x39edba00,0x39440000,0xb9ed3a00,0xb9440000,
0x3944b9b5,0x39edb9b5,0xb94439b5,0xb9ed39b5,0xb98e0000,0x39d5ba00,0x39d5ba00,0x398e0000,0xb9fb39ed,0xb8c8b944,0xb8c8b944,0x39fbb9ed,
0xb8c839b5,0xb9fb39b5,0xb9fb39b5,0x38c8b9b5,0x39d5b944,0xb98e39ed,0xb98e39ed,0xb9d53944,0x39b50000,0xb9b53a00,0x39b50000,0xb9b53a00,
0x39b5ba00,0x39b50000,0x39b5ba00,0x39b50000,0xb9b50000,0x39b5ba00,0xb9b50000,0x39b5ba00,0xb9b53a00,0xb9b50000,0xb9b53a00,0xb9b50000,
0xb9d50000,0x398eba00,0xb98e3a00,0xb9d50000,0xb8c839ed,0xb9fb3944,0x39fbb944,0xb8c839ed,0x39fbb9b5,0x38c839b5,0xb8c8b9b5,0x39fbb9b5,
0xb98eb944,0x39d5b9ed,0xb9d539ed,0xb98eb944,0x39ed0000,0xb9443a00,0xb9ed0000,0x3944ba00,0xb944b9b5,0x39edb9b5,0x394439b5,0xb9ed39b5,
0xb9443a00,0xb9ed0000,0x3944ba00,0x39ed0000,0x39edb9b5,0x394439b5,0xb9ed39b5,0xb944b9b5,0xb9fb0000,0x38c8ba00,0x38c8ba00,0x39fb0000,
0x39d53944,0xb98e39ed,0xb98e39ed,0xb9d5b944,0xb98eb9b5,0x39d5b9b5,0x39d5b9b5,0x398e39b5,0x38c839ed,0xb9fb3944,0xb9fb3944,0xb8c8b9ed,
0x3a000000,0x3a00,0x3a000000,0x3a00,0xba000000,0xba00,0xba000000,0xba00,0x3a000000,0x3a00,0x3a000000,0x3a00,
0xba000000,0xba00,0xba000000,0xba00,0xb9fb0000,0xb8c8ba00,0x38c83a00,0xb9fb0000,0x39d5b944,0x398e39ed,0xb98eb9ed,0x39d5b944,
0xb98e39b5,0xb9d5b9b5,0x39d539b5,0xb98e39b5,0x38c8b9ed,0x39fb3944,0xb9fbb944,0x38c8b9ed,0x39ed0000,0x39443a00,0xb9ed0000,0xb944ba00,
0xb94439b5,0xb9edb9b5,0x3944b9b5,0x39ed39b5,0xb944ba00,0x39ed0000,0x39443a00,0xb9ed0000,0x39ed39b5,0xb94439b5,0xb9edb9b5,0x3944b9b5,
0xb9d50000,0xb98eba00,0xb98eba00,0x39d50000,0xb8c8b9ed,0x39fb3944,0x39fb3944,0x38c839ed,0x39fb39b5,0xb8c839b5,0xb8c839b5,0xb9fbb9b5,
0xb98e3944,0xb9d5b9ed,0xb9d5b9ed,0x398eb944,0x39b50000,0x39b53a00,0x39b50000,0x39b53a00,0x39b53a00,0xb9b50000,0x39b53a00,0xb9b50000,
0xb9b50000,0xb9b5ba00,0xb9b50000,0xb9b5ba00,0xb9b5ba00,0x39b50000,0xb9b5ba00,0x39b50000,0xb98e0000,0xb9d5ba00,0x39d53a00,0xb98e0000,
0xb9fbb9ed,0x38c8b944,0xb8c83944,0xb9fbb9ed,0xb8c8b9b5,0x39fb39b5,0xb9fbb9b5,0xb8c8b9b5,0x39d53944,0x398e39ed,0xb98eb9ed,0x39d53944,
0x39440000,0x39ed3a00,0xb9440000,0xb9edba00,0x39ed39b5,0x394439b5,0xb9edb9b5,0xb944b9b5,0x39ed3a00,0xb9440000,0xb9edba00,0x39440000,
0x394439b5,0xb9edb9b5,0xb944b9b5,0x39ed39b5,0xb8c80000,0xb9fbba00,0xb9fbba00,0x38c80000,0xb98eb944,0xb9d5b9ed,0xb9d5b9ed,0x398e3944,
0xb9d5b9b5,0xb98eb9b5,0xb98eb9b5,0x39d539b5,0xb9fbb9ed,0xb8c8b944,0xb8c8b944,0x39fb39ed,
};
__device__ __align__(128) const uint32_t T_tw640i[512] = {
0x3acccccd,0x0,0x3accca46,0x3780ad75,0x3accc2b2,0x3800abdf,0x3accb610,0x3840fdd6,0x3acca461,0x3880a585,0x3acc8da6,0x38a0c8f3,
0x3acc71de,0x38c0e869,0x3acc510b,0x38e1031c,0x3acc2b2e,0x39008c21,0x3acc0047,0x39109388,0x3acbd057,0x3920975e,0x3acb9b60,0x3930973e,
0x3acb6163,0x394092c2,0x3acb2261,0x39508986,0x3acade5d,0x39607b24,0x3aca9556,0x39706739,0x3aca4751,0x398026af,0x3ac9f44d,0x39881699,
0x3ac99c4e,0x39900327,0x3ac93f55,0x3997ec27,0x3ac8dd65,0x399fd168,0x3ac87681,0x39a7b2b7,0x3ac80aaa,0x39af8fe3,0x3ac799e3,0x39b768ba,
0x3ac72430,0x39bf3d0b,0x3ac6a993,0x39c70ca3,0x3ac62a0f,0x39ced752,0x3ac5a5a8,0x39d69ce7,0x3ac51c60,0x39de5d30,0x3ac48e3a,0x39e617fd,
0x3ac3fb3c,0x39edcd1c,0x3ac36367,0x39f57c5d,0x3ac2c6c0,0x39fd2590,0x3ac2254b,0x3a026442,0x3ac17f0c,0x3a063284,0x3ac0d407,0x3a09fd76,
0x3ac0243f,0x3a0dc501,0x3abf6fba,0x3a11890c,0x3abeb67b,0x3a154980,0x3abdf888,0x3a190646,0x3abd35e5,0x3a1cbf44,0x3abc6e97,0x3a207465,
0x3abba2a3,0x3a242590,0x3abad20d,0x3a27d2ae,0x3ab9fcdb,0x3a2b7ba8,0x3ab92313,0x3a2f2067,0x3ab844b9,0x3a32c0d3,0x3ab761d3,0x3a365cd7,
0x3ab67a67,0x3a39f45b,0x3ab58e7a,0x3a3d8748,0x3ab49e13,0x3a411588,0x3ab3a936,0x3a449f04,0x3ab2afeb,0x3a4823a7,0x3ab1b237,0x3a4ba359,
0x3ab0b021,0x3a4f1e05,0x3aafa9af,0x3a529394,0x3aae9ee7,0x3a5603f2,0x3aad8fd0,0x3a596f08,0x3aac7c70,0x3a5cd4c0,0x3aab64d0,0x3a603506,
0x3aaa48f4,0x3a638fc3,0x3aa928e5,0x3a66e4e3,0x3aa804aa,0x3a6a3450,0x3aa6dc49,0x3a6d7df6,0x3acccccd,0x0,0x3accc2b2,0x3800abdf,
0x3acca461,0x3880a585,0x3acc71de,0x38c0e869,0x3acc2b2e,0x39008c21,0x3acbd057,0x3920975e,0x3acb6163,0x394092c2,0x3acade5d,0x39607b24,
0x3aca4751,0x398026af,0x3ac99c4e,0x39900327,0x3ac8dd65,0x399fd168,0x3ac80aaa,0x39af8fe3,0x3ac72430,0x39bf3d0b,0x3ac62a0f,0x39ced752,
0x3ac51c60,0x39de5d30,0x3ac3fb3c,0x39edcd1c,0x3ac2c6c0,0x39fd2590,0x3ac17f0c,0x3a063284,0x3ac0243f,0x3a0dc501,0x3abeb67b,0x3a154980,
0x3abd35e5,0x3a1cbf44,0x3abba2a3,0x3a242590,0x3ab9fcdb,0x3a2b7ba8,0x3ab844b9,0x3a32c0d3,0x3ab67a67,0x3a39f45b,0x3ab49e13,0x3a411588,
0x3ab2afeb,0x3a4823a7,0x3ab0b021,0x3a4f1e05,0x3aae9ee7,0x3a5603f2,0x3aac7c70,0x3a5cd4c0,0x3aaa48f4,0x3a638fc3,0x3aa804aa,0x3a6a3450,
0x3aa5afca,0x3a70c1c0,0x3aa34a91,0x3a77376d,0x3aa0d539,0x3a7d94b5,0x3a9e5003,0x3a81ec7b,0x3a9bbb2c,0x3a8501c8,0x3a9916f7,0x3a8809f5,
0x3a9663a6,0x3a8b04b5,0x3a93a17d,0x3a8df1bd,0x3a90d0c3,0x3a90d0c3,0x3a8df1bd,0x3a93a17d,0x3a8b04b5,0x3a9663a6,0x3a8809f5,0x3a9916f7,
0x3a8501c8,0x3a9bbb2c,0x3a81ec7b,0x3a9e5003,0x3a7d94b5,0x3aa0d539,0x3a77376d,0x3aa34a91,0x3a70c1c0,0x3aa5afca,0x3a6a3450,0x3aa804aa,
0x3a638fc3,0x3aaa48f4,0x3a5cd4c0,0x3aac7c70,0x3a5603f2,0x3aae9ee7,0x3a4f1e05,0x3ab0b021,0x3a4823a7,0x3ab2afeb,0x3a411588,0x3ab49e13,
0x3a39f45b,0x3ab67a67,0x3a32c0d3,0x3ab844b9,0x3a2b7ba8,0x3ab9fcdb,0x3a242590,0x3abba2a3,0x3a1cbf44,0x3abd35e5,0x3a154980,0x3abeb67b,
0x3a0dc501,0x3ac0243f,0x3a063284,0x3ac17f0c,0x3acccccd,0x0,0x3accb610,0x3840fdd6,0x3acc71de,0x38c0e869,0x3acc0047,0x39109388,
0x3acb6163,0x394092c2,0x3aca9556,0x39706739,0x3ac99c4e,0x39900327,0x3ac87681,0x39a7b2b7,0x3ac72430,0x39bf3d0b,0x3ac5a5a8,0x39d69ce7,
0x3ac3fb3c,0x39edcd1c,0x3ac2254b,0x3a026442,0x3ac0243f,0x3a0dc501,0x3abdf888,0x3a190646,0x3abba2a3,0x3a242590,0x3ab92313,0x3a2f2067,
0x3ab67a67,0x3a39f45b,0x3ab3a936,0x3a449f04,0x3ab0b021,0x3a4f1e05,0x3aad8fd0,0x3a596f08,0x3aaa48f4,0x3a638fc3,0x3aa6dc49,0x3a6d7df6,
0x3aa34a91,0x3a77376d,0x3a9f9496,0x3a805d00,0x3a9bbb2c,0x3a8501c8,0x3a97bf2e,0x3a898908,0x3a93a17d,0x3a8df1bd,0x3a8f6305,0x3a923aee,
0x3a8b04b5,0x3a9663a6,0x3a868788,0x3a9a6af9,0x3a81ec7b,0x3a9e5003,0x3a7a6928,0x3aa211e5,0x3a70c1c0,0x3aa5afca,0x3a66e4e3,0x3aa928e5,
0x3a5cd4c0,0x3aac7c70,0x3a529394,0x3aafa9af,0x3a4823a7,0x3ab2afeb,0x3a3d8748,0x3ab58e7a,0x3a32c0d3,0x3ab844b9,0x3a27d2ae,0x3abad20d,
0x3a1cbf44,0x3abd35e5,0x3a11890c,0x3abf6fba,0x3a063284,0x3ac17f0c,0x39f57c5d,0x3ac36367,0x39de5d30,0x3ac51c60,0x39c70ca3,0x3ac6a993,
0x39af8fe3,0x3ac80aaa,0x3997ec27,0x3ac93f55,0x398026af,0x3aca4751,0x39508986,0x3acb2261,0x3920975e,0x3acbd057,0x38e1031c,0x3acc510b,
0x3880a585,0x3acca461,0x3780ad75,0x3accca46,0xb800abdf,0x3accc2b2,0xb8a0c8f3,0x3acc8da6,0xb9008c21,0x3acc2b2e,0xb930973e,0x3acb9b60,
0xb9607b24,0x3acade5d,0xb9881699,0x3ac9f44d,0xb99fd168,0x3ac8dd65,0xb9b768ba,0x3ac799e3,0xb9ced752,0x3ac62a0f,0xb9e617fd,0x3ac48e3a,
0x3acccccd,0x0,0x3acca461,0x3880a585,0x3acc2b2e,0x39008c21,0x3acb6163,0x394092c2,0x3aca4751,0x398026af,0x3ac8dd65,0x399fd168,
0x3ac72430,0x39bf3d0b,0x3ac51c60,0x39de5d30,0x3ac2c6c0,0x39fd2590,0x3ac0243f,0x3a0dc501,0x3abd35e5,0x3a1cbf44,0x3ab9fcdb,0x3a2b7ba8,
0x3ab67a67,0x3a39f45b,0x3ab2afeb,0x3a4823a7,0x3aae9ee7,0x3a5603f2,0x3aaa48f4,0x3a638fc3,0x3aa5afca,0x3a70c1c0,0x3aa0d539,0x3a7d94b5,
0x3a9bbb2c,0x3a8501c8,0x3a9663a6,0x3a8b04b5,0x3a90d0c3,0x3a90d0c3,0x3a8b04b5,0x3a9663a6,0x3a8501c8,0x3a9bbb2c,0x3a7d94b5,0x3aa0d539,
0x3a70c1c0,0x3aa5afca,0x3a638fc3,0x3aaa48f4,0x3a5603f2,0x3aae9ee7,0x3a4823a7,0x3ab2afeb,0x3a39f45b,0x3ab67a67,0x3a2b7ba8,0x3ab9fcdb,
0x3a1cbf44,0x3abd35e5,0x3a0dc501,0x3ac0243f,0x39fd2590,0x3ac2c6c0,0x39de5d30,0x3ac51c60,0x39bf3d0b,0x3ac72430,0x399fd168,0x3ac8dd65,
0x398026af,0x3aca4751,0x394092c2,0x3acb6163,0x39008c21,0x3acc2b2e,0x3880a585,0x3acca461,0x1fe1e84f,0x3acccccd,0xb880a585,0x3acca461,
0xb9008c21,0x3acc2b2e,0xb94092c2,0x3acb6163,0xb98026af,0x3aca4751,0xb99fd168,0x3ac8dd65,0xb9bf3d0b,0x3ac72430,0xb9de5d30,0x3ac51c60,
0xb9fd2590,0x3ac2c6c0,0xba0dc501,0x3ac0243f,0xba1cbf44,0x3abd35e5,0xba2b7ba8,0x3ab9fcdb,0xba39f45b,0x3ab67a67,0xba4823a7,0x3ab2afeb,
0xba5603f2,0x3aae9ee7,0xba638fc3,0x3aaa48f4,0xba70c1c0,0x3aa5afca,0xba7d94b5,0x3aa0d539,0xba8501c8,0x3a9bbb2c,0xba8b04b5,0x3a9663a6,
0xba90d0c3,0x3a90d0c3,0xba9663a6,0x3a8b04b5,0xba9bbb2c,0x3a8501c8,0xbaa0d539,0x3a7d94b5,
};

__device__ __forceinline__ uint32_t badd2(uint32_t a, uint32_t b) { uint32_t r; asm("add.rn.bf16x2 %0, %1, %2;" : "=r"(r) : "r"(a), "r"(b)); return r; }
__device__ __forceinline__ uint32_t bsub2(uint32_t a, uint32_t b) { uint32_t r; asm("sub.rn.bf16x2 %0, %1, %2;" : "=r"(r) : "r"(a), "r"(b)); return r; }
__device__ __forceinline__ uint32_t bmul2(uint32_t a, uint32_t b) { uint32_t r; asm("mul.rn.bf16x2 %0, %1, %2;" : "=r"(r) : "r"(a), "r"(b)); return r; }
__device__ __forceinline__ uint32_t bfma2(uint32_t a, uint32_t b, uint32_t c) { uint32_t r; asm("fma.rn.bf16x2 %0, %1, %2, %3;" : "=r"(r) : "r"(a), "r"(b), "r"(c)); return r; }
__device__ __forceinline__ uint32_t gelu2(uint32_t t) {
  const float x0 = bf_lo(t), x1 = bf_hi(t);
  constexpr float K1 = -2.f * 0.7978845608028654f * 1.4426950408889634f, K2 = K1 * 0.044715f;
  float e0, e1, r;
  const float a0 = fminf(x0 * fmaf(K2, x0 * x0, K1), 60.f), a1 = fminf(x1 * fmaf(K2, x1 * x1, K1), 60.f);
  asm("ex2.approx.ftz.f32 %0, %1;" : "=f"(e0) : "f"(a0));
  asm("ex2.approx.ftz.f32 %0, %1;" : "=f"(e1) : "f"(a1));
  const float d0 = 1.f + e0, d1 = 1.f + e1;
  asm("rcp.approx.ftz.f32 %0, %1;" : "=f"(r) : "f"(d0 * d1));
  return pack_bf16(x0 * d1 * r, x1 * d0 * r);
}
__device__ __forceinline__ float gelu_tanh(float x) { return bf_lo(gelu2(pack_bf16(x, x))); }

template<int WHICH> struct GemmCfg;
template<> struct GemmCfg<1> { static constexpr int BN = 144, ABYTES = 16384, BBYTES = 24576, BTX = 64 * 144 * 2 + 0, EPI_PITCH = 144; };
template<> struct GemmCfg<2> { static constexpr int BN = 160, ABYTES = 16384, BBYTES = 20480, BTX = 20480, EPI_PITCH = 160; };

template<int WHICH, int G, int STAGES>
struct GemmSmem {
  static constexpr int BN = GemmCfg<WHICH>::BN;
  static constexpr int STAGE_BYTES = GemmCfg<WHICH>::ABYTES + GemmCfg<WHICH>::BBYTES;
  static constexpr int RED_BYTES = (4 + ((BN / 16 - 5) * 3 + 3) / 4) * 4096;
  static constexpr int OFF_RED = STAGES * STAGE_BYTES;
  static constexpr int NKB = WHICH == 1 ? 16 : 14;
  static constexpr int OFF_X2 = (NKB % STAGES) * STAGE_BYTES;
  static constexpr int OFF_LP = ((NKB + 1) % STAGES) * STAGE_BYTES;
  static constexpr int OFF_BAR = OFF_RED + RED_BYTES;
  static constexpr int TOTAL = OFF_BAR + 256 + 1024;
};

template<int WHICH, int G, int STAGES>
__global__ void __launch_bounds__(512, 1)
gemm_kernel(const __grid_constant__ CUtensorMap tmA, const __grid_constant__ CUtensorMap tmB, const __grid_constant__ CUtensorMap tmO, const __grid_constant__ CUtensorMap tmX2,
            const bf16* __restrict__ bias, const bf16* __restrict__ x2, const bf16* __restrict__ gate, bf16* __restrict__ outp)
{
  using SM = GemmSmem<WHICH, G, STAGES>;
  constexpr int BN = SM::BN, NACC = BN / 2, HALF = NACC / 2;
  extern __shared__ uint8_t smem_raw[];
  const uint32_t sbase = (smem_u32(smem_raw) + 1023) & ~1023u;
  const uint32_t bar_full = sbase + SM::OFF_BAR, bar_empty = bar_full + 8 * STAGES, bar_red = bar_empty + 8 * STAGES;
  constexpr int NBLK = HALF / 4, NCONS = 5, NVB = ((NBLK - NCONS) * 3 + 3) / 4;
  const int tid = threadIdx.x, wg = tid >> 7, warp = tid >> 5, lane = tid & 31;
  const uint32_t rank = cluster_rank();
  const int g = rank % G, kh = rank / G;
  const int cid = blockIdx.x / (2 * G);
  int m0, n0t, nkb, kb0;
  if (WHICH == 1) { m0 = (cid % 5) * 128; n0t = (cid / 5) * G + g; nkb = 16; kb0 = kh * 16; }
  else { n0t = cid % 4; m0 = ((cid / 4) * G + g) * 128; nkb = 14; kb0 = 0; }

  if (tid == 0) TL(3 + WHICH, 0);
  if (warp == 0) CK(3 + WHICH, 0);
  if (tid == 0) {
    for (int s = 0; s < STAGES; s++) { mbar_init(bar_full + 8 * s, 2); mbar_init(bar_empty + 8 * s, 2 * G); }
    for (int k = 0; k < 5; k++) mbar_init(bar_red + 8 * k, 1);
    fence_mbar_init();
    mbar_expect_tx(bar_red, 4 * 4096); mbar_expect_tx(bar_red + 8, NVB * 4096);
  }
  __syncthreads();
  cluster_arrive_relaxed(); cluster_wait();
  pdl_trigger();
  if (tid == 0) TL(3 + WHICH, 1);

  constexpr int NH = BN / 2;
  constexpr int NB = NH / 8;
  constexpr int PITCH = NH * 2;
  const int ft = tid & 255;
  const int fw = ft >> 5;
  const int i = lane >> 2, c = lane & 3;
  const int row = fw * 16 + i;
  const int col0 = n0t * BN + kh * NH;
  const uint32_t stg = sbase + SM::OFF_X2;
  const uint32_t* xs = reinterpret_cast<const uint32_t*>(smem_raw + (stg - smem_u32(smem_raw)) + row * PITCH) + c;
  const uint4* rp = reinterpret_cast<const uint4*>(smem_raw + (sbase - smem_u32(smem_raw)) + SM::OFF_RED) + ft;
  float4* lp = reinterpret_cast<float4*>(smem_raw + (sbase - smem_u32(smem_raw)) + SM::OFF_LP) + ft;
  const uint32_t a0 = stg + (fw * 16 + (lane & 7) + ((lane >> 3) & 1) * 8) * PITCH;
  uint32_t bs0 = 0, bs1 = 0;
  if constexpr (WHICH == 2) {
    const uint32_t b0 = __ldg(reinterpret_cast<const uint16_t*>(bias) + m0 + row), b1 = __ldg(reinterpret_cast<const uint16_t*>(bias) + m0 + row + 8);
    bs0 = b0 | (b0 << 16); bs1 = b1 | (b1 << 16);
  }
  auto fin = [&](int mm, float4 o, uint32_t bq, uint32_t w0, uint32_t w1, uint32_t w2) {
    float4 v;
    v.x = __uint_as_float(w0 & 0xffffff00u); v.y = __uint_as_float(w1 & 0xffffff00u); v.z = __uint_as_float(w2 & 0xffffff00u);
    v.w = __uint_as_float(__byte_perm(__byte_perm(w0, w1, 0x0040), w2, 0x4100) & 0xffffff00u);
    uint32_t t0 = pack_bf16(o.x + v.x, o.y + v.y), t1 = pack_bf16(o.z + v.z, o.w + v.w), p0, p1;
    if constexpr (WHICH == 1) {
      p0 = gelu2(badd2(t0, bq)); p1 = gelu2(badd2(t1, bq));
    } else {
      p0 = badd2(xs[mm * 4], bmul2(bq, badd2(t0, bs0)));
      p1 = badd2(xs[8 * (PITCH / 4) + mm * 4], bmul2(bq, badd2(t1, bs1)));
      __syncwarp();
    }
    stmatrix_x2(a0 + mm * 16, p0, p1);
  };
  auto load_bq = [&](int mm) -> uint32_t {
    if constexpr (WHICH == 1) return __ldg(reinterpret_cast<const uint32_t*>(bias + col0 + 2 * c) + mm * 4);
    else return __ldcg(reinterpret_cast<const uint32_t*>(gate + col0 + 2 * c) + mm * 4);
  };

  if (wg >= 2) {
    if (warp == 8 && lane == 0) {
      prefetch_tmap(WHICH == 1 ? &tmB : &tmA);
      int s = 0, ph = 1;
#pragma unroll 1
      for (int kb = 0; kb < nkb; kb++) {
        mbar_wait(bar_empty + 8 * s, ph);
        const uint32_t st = sbase + s * SM::STAGE_BYTES, bar = bar_full + 8 * s;
        const int k0 = (WHICH == 1 ? kb0 + kb : kb == 0 ? 13 : kh ? 13 + kb : kb - 1) * 64;
        if (WHICH == 1) {
          mbar_expect_tx(bar, 3 * 8192);
#pragma unroll
          for (int j = 0; j < 3; j++) tma_load_3d(st + 16384 + j * 8192, &tmB, j * 64, n0t, k0, bar);
        } else {
          mbar_expect_tx(bar, 16384);
          tma_load_3d(st, &tmA, 0, k0, m0 >> 6, bar);
        }
        if (kb == 0) mbar_wait(bar_red + 32, 0);
        if (++s == STAGES) { s = 0; ph ^= 1; }
      }
    } else if (WHICH == 1 && warp == 10 && lane == 0) {
      mbar_wait(bar_full + 8 * (10 % STAGES), (10 / STAGES) & 1);
      const char* base = reinterpret_cast<const char*>(outp);
      if (blockIdx.x < 128) {
        const int r = blockIdx.x * 4;
        const int row = r < 256 ? r : 896 + (r - 256);
        prefetch_l2_bulk(base + (size_t)row * 4096, 16384);
      }
    } else if (warp == 9 && lane == 0) {
      prefetch_tmap(WHICH == 1 ? &tmA : &tmB);
      const uint16_t mask = (uint16_t)(((1u << G) - 1) << (kh * G));
      pdl_wait();
      TL(5 + WHICH, 1);
      int s = 0, ph = 1;
#pragma unroll 1
      for (int kb = 0; kb < nkb; kb++) {
        mbar_wait(bar_empty + 8 * s, ph);
        const uint32_t st = sbase + s * SM::STAGE_BYTES, bar = bar_full + 8 * s;
        const int k0 = (WHICH == 1 ? kb0 + kb : kb == 0 ? 13 : kh ? 13 + kb : kb - 1) * 64;
        if (WHICH == 1) {
          mbar_expect_tx(bar, 16384);
          constexpr int R = 128 / G;
          const int c = (g * R) >> 6, r0 = (g * R) & 63;
          if (G == 1) { tma_load_2d(st, &tmA, m0, k0, bar); tma_load_2d(st + 8192, &tmA, m0 + 64, k0, bar); }
          else tma_load_2d_mc(st + g * R * 128, &tmA, m0 + c * 64, k0 + r0, bar, mask);
        } else {
          mbar_expect_tx(bar, 20480);
          constexpr int R = 160 / G;
          if (G == 1) tma_load_2d(st + 16384, &tmB, k0, n0t * 160, bar);
          else tma_load_2d_mc(st + 16384 + g * R * 128, &tmB, k0, n0t * 160 + g * R, bar, mask);
        }
        if (kb == 0) mbar_arrive(bar_red + 32);
        if (++s == STAGES) { s = 0; ph ^= 1; }
      }
      if (WHICH == 2) {
        mbar_wait(bar_empty + 8 * s, ph);
        mbar_expect_tx(bar_red + 24, 128 * 160); tma_load_2d(sbase + SM::OFF_X2, &tmX2, n0t * BN + kh * (BN / 2), m0, bar_red + 24);
      }
    }
    __syncwarp();
    if (WHICH == 2) pdl_wait();
    uint32_t bq[NB - NCONS];
#pragma unroll
    for (int mm = NCONS; mm < NB; mm++) bq[mm - NCONS] = load_bq(mm);
    asm volatile("bar.sync 2, 512;" ::: "memory");
    if (WHICH == 2) mbar_wait(bar_red + 24, 0);
    mbar_wait_cluster(bar_red + 8, 0);
    {
      uint32_t pw[NVB * 4];
#pragma unroll
      for (int k = 0; k < NVB; k++) { const uint4 q = rp[(4 + k) * 256]; pw[4 * k] = q.x; pw[4 * k + 1] = q.y; pw[4 * k + 2] = q.z; pw[4 * k + 3] = q.w; }
#pragma unroll
      for (int mm = NCONS; mm < NB; mm++) fin(mm, lp[(mm - NCONS) * 256], bq[mm - NCONS], pw[3 * (mm - NCONS)], pw[3 * (mm - NCONS) + 1], pw[3 * (mm - NCONS) + 2]);
    }
    fence_proxy_async();
    asm volatile("bar.sync 1, 512;" ::: "memory");
  } else {
    float acc[NACC];
    uint32_t bq[NCONS];
    if (WHICH == 2) pdl_wait();
#pragma unroll
    for (int mm = 0; mm < NCONS; mm++) bq[mm] = load_bq(mm);
    int s = 0, ph = 0;
    const uint64_t dA0 = make_desc_sw128(sbase + wg * 8192, 8192, 1024);
    const uint64_t dB0 = WHICH == 1 ? make_desc_sw128(sbase + 16384, 8192, 1024) : make_desc_sw128(sbase + 16384, 16, 1024);
    if constexpr (WHICH == 2) {
      mbar_wait(bar_full, 0);
      if (tid == 0) TL(3 + WHICH, 2);
      wgmma_fence();
      wgmma_ss_n160<1, 0>(acc, dA0 + kh * 256, dB0 + kh * 4, 0);
      wgmma_ss_n160<1, 0>(acc, dA0 + kh * 256 + 128, dB0 + kh * 4 + 2, 1);
      wgmma_commit();
      s = 1;
    }
#pragma unroll 1
    for (int kb = (WHICH == 2 ? 1 : 0); kb < nkb; kb++) {
      mbar_wait(bar_full + 8 * s, ph);
      if (WHICH == 1 && kb == 0 && tid == 0) TL(3 + WHICH, 2);
      if (warp == 0) CK(3 + WHICH, 1 + kb);
      const uint64_t so = (uint64_t)(s * (SM::STAGE_BYTES >> 4));
      wgmma_fence();
#pragma unroll
      for (int kk = 0; kk < 4; kk++) {
        if constexpr (WHICH == 1) wgmma_ss_n144<1, 1>(acc, dA0 + so + kk * 128, dB0 + so + kk * 128, (kb | kk) != 0);
        else wgmma_ss_n160<1, 0>(acc, dA0 + so + kk * 128, dB0 + so + kk * 2, 1);
      }
      wgmma_commit();
      if (kb > 0) {
        wgmma_wait<1>();
        const int ps = (s == 0) ? STAGES - 1 : s - 1;
        if ((tid & 127) < G) {
          if (G == 1) mbar_arrive(bar_empty + 8 * ps);
          else mbar_arrive_cluster(mapa(bar_empty + 8 * ps, kh * G + (tid & 127)));
        }
      }
      if (++s == STAGES) { s = 0; ph ^= 1; }
    }
    wgmma_wait<0>();
    reg_fence(acc);
    if (tid == 0) TL(3 + WHICH, 3);
    if (warp == 0) CK(3 + WHICH, 17);
    {
      const uint32_t peer = (rank + G) % (2 * G);
      const uint32_t dst = mapa(sbase + SM::OFF_RED, peer) + tid * 16;
      const uint32_t rbar = mapa(bar_red, peer);
      uint32_t pw[16 + NVB * 4];
#pragma unroll
      for (int k = 0; k < 16 + NVB * 4; k++) pw[k] = 0u;
#pragma unroll
      for (int j = 0; j < NBLK; j++) {
        const uint32_t f0 = __float_as_uint(kh == 0 ? acc[HALF + 4 * j] : acc[4 * j]) + 0x80u, f1 = __float_as_uint(kh == 0 ? acc[HALF + 4 * j + 1] : acc[4 * j + 1]) + 0x80u;
        const uint32_t f2 = __float_as_uint(kh == 0 ? acc[HALF + 4 * j + 2] : acc[4 * j + 2]) + 0x80u, f3 = __float_as_uint(kh == 0 ? acc[HALF + 4 * j + 3] : acc[4 * j + 3]) + 0x80u;
        const int o = j < NCONS ? 3 * j : 16 + 3 * (j - NCONS);
        pw[o] = __byte_perm(f0, f3, 0x3215); pw[o + 1] = __byte_perm(f1, f3, 0x3216); pw[o + 2] = __byte_perm(f2, f3, 0x3217);
      }
#pragma unroll
      for (int k = 0; k < 4 + NVB; k++)
        st_async_v4(dst + k * 4096, __uint_as_float(pw[4 * k]), __uint_as_float(pw[4 * k + 1]), __uint_as_float(pw[4 * k + 2]), __uint_as_float(pw[4 * k + 3]), rbar + (k < 4 ? 0 : 8));
      if (kh) {
#pragma unroll
        for (int j = 0; j < HALF; j++) acc[j] = acc[HALF + j];
      }
    }
    asm volatile("bar.sync 3, 256;" ::: "memory");
#pragma unroll
    for (int mm = NCONS; mm < NB; mm++) lp[(mm - NCONS) * 256] = make_float4(acc[4 * mm], acc[4 * mm + 1], acc[4 * mm + 2], acc[4 * mm + 3]);
    asm volatile("bar.arrive 2, 512;" ::: "memory");
    if (WHICH == 2) mbar_wait(bar_red + 24, 0);
    mbar_wait_cluster(bar_red, 0);
    if (tid == 0) TL(3 + WHICH, 4);
    if (warp == 0) CK(3 + WHICH, 18);
    {
      uint32_t pw[16];
#pragma unroll
      for (int k = 0; k < 4; k++) { const uint4 q = rp[k * 256]; pw[4 * k] = q.x; pw[4 * k + 1] = q.y; pw[4 * k + 2] = q.z; pw[4 * k + 3] = q.w; }
#pragma unroll
      for (int mm = 0; mm < NCONS; mm++)
        fin(mm, make_float4(acc[4 * mm], acc[4 * mm + 1], acc[4 * mm + 2], acc[4 * mm + 3]), bq[mm], pw[3 * mm], pw[3 * mm + 1], pw[3 * mm + 2]);
    }
    fence_proxy_async();
    asm volatile("bar.sync 1, 512;" ::: "memory");
    if (tid == 0) {
      TL(3 + WHICH, 5);
      CK(3 + WHICH, 19);
      tma_store_2d(&tmO, stg, col0, m0);
      bulk_commit();
      bulk_wait_read0();
      TL(3 + WHICH, 6);
      CK(3 + WHICH, 20);
    }
  }
  cluster_arrive_relaxed(); cluster_wait();
}

constexpr int S_ = 2048, D_ = 640, F_ = 1728, NC_ = 321;

__device__ __align__(128) bf16 g_mod[3840];
__device__ __align__(1024) bf16 g_X1[2 * NC_ * S_];
__device__ __align__(1024) bf16 g_Z[2 * NC_ * S_];
__device__ __align__(1024) uint32_t g_Wt[NC_ * S_];
__device__ __align__(1024) bf16 g_x2[S_ * D_];
__device__ __align__(1024) bf16 g_h3[S_ * D_];
__device__ __align__(1024) bf16 g_u[D_ * F_];
constexpr int NREP = 16;
__device__ __align__(128) float g_modp[4 * 1280];

__device__ __forceinline__ unsigned long long ld_rlx64(const unsigned long long* p) { unsigned long long v; asm volatile("ld.relaxed.gpu.global.u64 %0,[%1];" : "=l"(v) : "l"(p) : "memory"); return v; }
__device__ __forceinline__ void st_rlx64(unsigned long long* p, unsigned long long v) { asm volatile("st.relaxed.gpu.global.u64 [%0],%1;" ::"l"(p), "l"(v) : "memory"); }
__device__ __forceinline__ ulonglong2 ld_rlx64x2(const unsigned long long* p) { ulonglong2 v; asm volatile("ld.relaxed.gpu.global.v2.u64 {%0,%1},[%2];" : "=l"(v.x), "=l"(v.y) : "l"(p) : "memory"); return v; }
__device__ __forceinline__ uint4 ld_rlx128(const uint32_t* p) { uint4 v; asm volatile("ld.relaxed.gpu.global.v4.u32 {%0,%1,%2,%3},[%4];" : "=r"(v.x), "=r"(v.y), "=r"(v.z), "=r"(v.w) : "l"(p) : "memory"); return v; }
__device__ __forceinline__ unsigned ld_rlx(const unsigned* p) { unsigned v; asm volatile("ld.relaxed.gpu.global.u32 %0,[%1];" : "=r"(v) : "l"(p) : "memory"); return v; }
__device__ __forceinline__ void red_rel(unsigned* p) { asm volatile("red.release.gpu.global.add.u32 [%0],1;" ::"l"(p) : "memory"); }
__device__ __forceinline__ void fence_acq_gpu() { asm volatile("fence.acq_rel.gpu;" ::: "memory"); }

__device__ __forceinline__ void src_to_col(int kp, int& col, bool& mirrored) {
  const int q = kp / 10, res = kp - 10 * q;
  mirrored = res > 5;
  col = res == 0 ? 256 + q : res == 5 ? 289 + q : res < 5 ? (res - 1) * 64 + q : (9 - res) * 64 + 63 - q;
}

__device__ __forceinline__ void layernorm_warp(uint32_t (&P)[10], int lane) {
  float g0[4] = {0.f, 0.f, 0.f, 0.f}, g1[4] = {0.f, 0.f, 0.f, 0.f}, gs[4] = {0.f, 0.f, 0.f, 0.f};
#pragma unroll
  for (int k = 0; k < 3; k++) {
    const uint32_t a0 = P[4 * k], a1 = P[4 * k + 1], a2 = k < 2 ? P[4 * k + 2] : 0u, a3 = k < 2 ? P[4 * k + 3] : 0u;
    mma16816(g0, a0, a1, a2, a3, a0, a2);
    mma16816(g1, a0, a1, a2, a3, a1, a3);
    mma16816(gs, a0, a1, a2, a3, 0x3f803f80u, 0x3f803f80u);
  }
  const int i = lane >> 2;
  float q = ((lane & 3) == (i >> 1)) ? ((i & 1) ? g0[1] + g1[3] : g0[0] + g1[2]) : 0.f;
  float s = gs[0] + gs[2];
  q += __shfl_xor_sync(0xffffffffu, q, 1); q += __shfl_xor_sync(0xffffffffu, q, 2);
#pragma unroll
  for (int o = 4; o < 32; o <<= 1) { q += __shfl_xor_sync(0xffffffffu, q, o); s += __shfl_xor_sync(0xffffffffu, s, o); }
  const float mean = s * (1.f / 640.f);
  const float var = bfr(fmaxf(fmaf(-mean, mean, q * (1.f / 640.f)), 0.f));
  float sd; asm("sqrt.approx.f32 %0, %1;" : "=f"(sd) : "f"(bfr(var + 1e-5f)));
  float rinv; asm("rcp.approx.f32 %0, %1;" : "=f"(rinv) : "f"(bfr(sd)));
  const uint32_t m2 = pack_bf16(mean, mean);
  const float rh = bfr(rinv);
  const uint32_t rhi = pack_bf16(rh, rh), rlo = pack_bf16(rinv - rh, rinv - rh);
#pragma unroll
  for (int k = 0; k < 10; k++) { const uint32_t d = bsub2(P[k], m2); P[k] = bfma2(d, rhi, bmul2(d, rlo)); }
}

constexpr float C1_ = 0.30901699437494745f, C2_ = -0.8090169943749475f, S1_ = 0.9510565162951535f, S2_ = 0.5877852522924731f;
constexpr uint32_t BF_ONE2 = 0x3f803f80u;

constexpr int K0_SMEM = 20480 + 512 + 64 + 1024;
__global__ void __launch_bounds__(128)
k0_kernel(const __grid_constant__ CUtensorMap tmWm  , const bf16* __restrict__ c)
{
  extern __shared__ uint8_t smem_raw[];
  uint8_t* sm = smem_raw + ((1024 - (smem_u32(smem_raw) & 1023)) & 1023);
  const uint32_t sb = smem_u32(sm);
  const int tid = threadIdx.x, w = tid >> 5, lane = tid & 31, b = blockIdx.x;
  const uint32_t bar = sb + 20480 + 512;
  if (tid == 0) {
    TL(0, 5);
    mbar_init(bar, 1); fence_mbar_init();
    mbar_expect_tx(bar, 20480);
    tma_load_2d(sb, &tmWm, (b % 20) * 64, (b / 20) * 160, bar);
  }
  pdl_trigger();
  if (tid < 80) {
    const uint32_t cp = __ldg(reinterpret_cast<const uint32_t*>(c) + (b / 20) * 80 + tid);
    const float c0 = bf_lo(cp), c1 = bf_hi(cp);
    reinterpret_cast<uint32_t*>(sm + 20480)[tid] = pack_bf16(__fdividef(c0, 1.f + __expf(-c0)), __fdividef(c1, 1.f + __expf(-c1)));
  }
  __syncthreads();
  mbar_wait(bar, 0);
  const int mid = lane >> 3, j = lane & 7;
  float d0[4] = {0.f, 0.f, 0.f, 0.f}, d1[4] = {0.f, 0.f, 0.f, 0.f};
  const uint32_t ba = sb + ((mid & 1) * 8 + j) * 128 + (((w * 2 + (mid >> 1)) ^ j) << 4);
  const uint32_t* sp = reinterpret_cast<const uint32_t*>(sm + 20480) + (lane & 3);
#pragma unroll
  for (int k = 0; k < 10; k++) {
    uint32_t bb[4];
    ldmatrix_x4_trans(bb, ba + k * 2048);
    const uint32_t a0 = sp[k * 8], a2 = sp[k * 8 + 4];
    mma16816(d0, a0, a0, a2, a2, bb[0], bb[1]);
    mma16816(d1, a0, a0, a2, a2, bb[2], bb[3]);
  }
  if (lane < 4) {
    float* gp = g_modp + (b / 20) * 1280 + (b % 20) * 64 + w * 16 + lane * 2;
    *reinterpret_cast<float2*>(gp) = make_float2(d0[0], d0[1]);
    *reinterpret_cast<float2*>(gp + 8) = make_float2(d1[0], d1[1]);
  }
  if (tid == 0) TL(0, 0);
}

constexpr int K1_OFF_AT = 0, K1_OFF_F = 24576, K1_OFF_G = 40960, K1_OFF_ST = 57344, K1_OFF_X = (K1_OFF_ST + 20736 + 1023) / 1024 * 1024, K1_OFF_MOD = K1_OFF_X + 20480,
              K1_OFF_RED = K1_OFF_MOD + 2560, K1_OFF_PART = K1_OFF_RED + 256, K1_OFF_SC = K1_OFF_PART + 512, K1_OFF_W = K1_OFF_SC + 1280, K1_OFF_WM = (K1_OFF_W + 21504 + 1023) / 1024 * 1024, K1_OFF_WT = (K1_OFF_WM + 20480 + 511) / 512 * 512, K1_OFF_BAR = K1_OFF_WT + 336 * 64;
constexpr int K1_SMEM = K1_OFF_BAR + 64 + 1024;

__global__ void __launch_bounds__(640, 1)
k1_kernel(const __grid_constant__ CUtensorMap tmX1  , const __grid_constant__ CUtensorMap tmWm  , const __grid_constant__ CUtensorMap tmWt  ,
          const __grid_constant__ CUtensorMap tmWr, const __grid_constant__ CUtensorMap tmWi  ,
          const bf16* __restrict__ x,
          const bf16* __restrict__ c, const bf16* __restrict__ w_mod, const bf16* __restrict__ wr, const bf16* __restrict__ wi)
{
  extern __shared__ uint8_t smem_raw[];
  uint8_t* sm = smem_raw + ((1024 - (smem_u32(smem_raw) & 1023)) & 1023);
  const uint32_t sb = smem_u32(sm);
  const int tid = threadIdx.x, wg = tid >> 7, warp = tid >> 5, lane = tid & 31;
  const int b = blockIdx.x, row0 = b * 16;
  const uint32_t bar = sb + K1_OFF_BAR;
  if (wg == 4) {
    const int t = tid - 512, w4 = warp & 3;
    if (w4 == 0) CK(0, 0);
    asm volatile("bar.sync 3, 640;" ::: "memory");
    if (t == 0) {
      mbar_wait(bar + 40, 0);
      mbar_expect_tx(bar + 8, 32768);
      bulk_load(sb + K1_OFF_F, T_F64, 16384, bar + 8);
      bulk_load(sb + K1_OFF_G, T_Gf, 16384, bar + 8);
      const int pp = (b >> 5) * 8 + (b & 7), kq = (b >> 3) & 3;
      mbar_expect_tx(bar + 16, 21504);
#pragma unroll 1
      for (int bx = 0; bx < 2; bx++) {
        const int x0 = ((pp * NC_) & ~7) + bx * 168;
        tma_load_2d(sb + K1_OFF_W + bx * 5376, &tmWr, x0, 16 * kq, bar + 16);
        tma_load_2d(sb + K1_OFF_W + 10752 + bx * 5376, &tmWi, x0, 16 * kq, bar + 16);
      }
    }
    __syncwarp();
    const int kq = (b >> 3) & 3, pp = (b >> 5) * 8 + (b & 7);
    const int od = (pp * NC_) & 7;
    mbar_wait(bar + 16, 0);
    if (t == 0) TL(0, 3);
    if (w4 == 0) CK(0, 3);
#pragma unroll 1
    for (int kp = t; kp < NC_; kp += 128) {
      int col; bool mir; src_to_col(kp, col, mir);
      const int ko = kp + od;
      const uint8_t* rp = sm + K1_OFF_W + (ko >= 168 ? 5376 + (ko - 168) * 2 : ko * 2);
      uint8_t* dst = sm + K1_OFF_WT + col * 64;
#pragma unroll
      for (int k = 0; k < 4; k++) {
        uint32_t v[4];
#pragma unroll
        for (int e = 0; e < 4; e++) {
          const uint8_t* q = rp + (8 * (e >> 1) + 2 * k + (e & 1)) * 336;
          v[e] = (uint32_t)*reinterpret_cast<const uint16_t*>(q) | ((uint32_t)*reinterpret_cast<const uint16_t*>(q + 10752) << 16);
        }
        *reinterpret_cast<uint4*>(dst + ((k ^ ((col >> 1) & 3)) << 4)) = make_uint4(v[0], v[1], v[2], v[3]);
      }
    }
    if (w4 == 0) CK(0, 4);
    fence_proxy_async();
    asm volatile("bar.sync 1, 128;" ::: "memory");
    if (w4 == 0) CK(0, 5);
    if (t == 0) {
      const int wo = ((b >> 5) * 128 + kq * 32 + (b & 7) * 4) * 4;
      tma_store_2d(&tmWt, sb + K1_OFF_WT, wo, 0);
      tma_store_2d(&tmWt, sb + K1_OFF_WT + 168 * 64, wo, 168);
      bulk_commit();
      TL(0, 4);
    }
    if (t == 0) { bulk_wait_read0(); TL(0, 1); CK(0, 9); }
    return;
  }
  if (warp == 0) CK(1, 0);
  if (tid == 0) {
    TL(1, 0);
#pragma unroll
    for (int k = 0; k < 5; k++) mbar_init(bar + 8 * k, 1);
    mbar_init(bar + 40, 10);
    fence_mbar_init();
    mbar_expect_tx(bar, 20480);
    bulk_load(sb + K1_OFF_X, x + (size_t)row0 * D_, 20480, bar);
  }
  pdl_trigger();
  float4 tw[4];
#pragma unroll
  for (int p = 0; p < 4; p++) tw[p] = __ldg(reinterpret_cast<const float4*>(T_tw640) + p * 32 + lane);
  if (warp == 0) CK(1, 1);
  asm volatile("bar.sync 3, 640;" ::: "memory");
  if (warp == 0) CK(1, 2);
  if (tid < 256) *reinterpret_cast<uint4*>(sm + K1_OFF_AT + 2 * 8192 + 4096 + tid * 16) = make_uint4(0, 0, 0, 0);
  else if (tid < 260) { const int R = NC_ + 256 + ((tid >> 1) & 1) * 32; *reinterpret_cast<uint4*>(sm + K1_OFF_ST + R * 32 + (tid & 1) * 16) = make_uint4(0, 0, 0, 0); }
  if (tid < 320) {
    pdl_wait();
    if (tid == 0) TL(0, 6);
    const uint32_t* gp = reinterpret_cast<const uint32_t*>(g_modp) + 4 * tid;
    uint4 v[4];
#pragma unroll
    for (int k = 0; k < 4; k++) v[k] = ld_rlx128(gp + k * 1280);
    if (lane == 0) mbar_arrive(bar + 40);
    const float s0 = (__uint_as_float(v[0].x) + __uint_as_float(v[1].x)) + (__uint_as_float(v[2].x) + __uint_as_float(v[3].x));
    const float s1 = (__uint_as_float(v[0].y) + __uint_as_float(v[1].y)) + (__uint_as_float(v[2].y) + __uint_as_float(v[3].y));
    const float s2 = (__uint_as_float(v[0].z) + __uint_as_float(v[1].z)) + (__uint_as_float(v[2].z) + __uint_as_float(v[3].z));
    const float s3 = (__uint_as_float(v[0].w) + __uint_as_float(v[1].w)) + (__uint_as_float(v[2].w) + __uint_as_float(v[3].w));
    uint32_t v0 = pack_bf16(s0, s1), v1 = pack_bf16(s2, s3);
    if (b == 0) *reinterpret_cast<uint2*>(g_mod + 4 * tid) = make_uint2(v0, v1);
    if (tid >= 160) { v0 = badd2(BF_ONE2, v0); v1 = badd2(BF_ONE2, v1); }
    *reinterpret_cast<uint2*>(sm + K1_OFF_MOD + 8 * tid) = make_uint2(v0, v1);
  }
  if (warp == 0) CK(1, 17);
  uint32_t P[10];
  if (warp == 0) CK(1, 5);
  mbar_wait(bar, 0);
  if (warp == 0) CK(1, 6);
  if (warp == 15) CK(1, 29);
  {
    const uint8_t* xp = sm + K1_OFF_X + warp * 1280 + lane * 4;
#pragma unroll
    for (int a = 0; a < 10; a++) P[a] = *reinterpret_cast<const uint32_t*>(xp + a * 128);
  }
  layernorm_warp(P, lane);
  asm volatile("bar.sync 2, 512;" ::: "memory");
  if (tid == 0) TL(1, 1);
  if (warp == 0) CK(1, 7);
  if (tid == 0) TL(1, 2);
  if (warp == 0) CK(1, 9);
  {
    const uint32_t* mp = reinterpret_cast<const uint32_t*>(sm + K1_OFF_MOD) + lane;
    float n[10][2];
#pragma unroll
    for (int a = 0; a < 10; a++) {
      const uint32_t h = badd2(bmul2(P[a], mp[320 + a * 32]), mp[a * 32]);
      n[a][0] = bf_lo(h); n[a][1] = bf_hi(h);
    }
    float Tr[6][2], Ti[6][2];
#pragma unroll
    for (int j = 0; j < 2; j++) {
      float e[5], o[5];
#pragma unroll
      for (int a = 0; a < 5; a++) { e[a] = n[a][j] + n[a + 5][j]; o[a] = (a & 1) ? n[a + 5][j] - n[a][j] : n[a][j] - n[a + 5][j]; }
      {
        const float s1 = e[1] + e[4], d1 = e[1] - e[4], s2 = e[2] + e[3], d2 = e[2] - e[3];
        Tr[0][j] = e[0] + s1 + s2;
        Tr[2][j] = fmaf(C2_, s2, fmaf(C1_, s1, e[0])); Ti[2][j] = fmaf(-S1_, d1, -S2_ * d2);
        Tr[4][j] = fmaf(C1_, s2, fmaf(C2_, s1, e[0])); Ti[4][j] = fmaf(-S2_, d1, S1_ * d2);
      }
      {
        const float s1 = o[1] + o[4], d1 = o[1] - o[4], s2 = o[2] + o[3], d2 = o[2] - o[3];
        Tr[5][j] = o[0] + s1 + s2;
        Tr[3][j] = fmaf(C2_, s2, fmaf(C1_, s1, o[0])); Ti[3][j] = fmaf(S1_, d1, S2_ * d2);
        Tr[1][j] = fmaf(C1_, s2, fmaf(C2_, s1, o[0])); Ti[1][j] = fmaf(S2_, d1, -S1_ * d2);
      }
    }
    const int rh = warp >> 3, ri = warp & 7;
    uint8_t* t = sm + K1_OFF_AT + (16 * rh + ri) * 128 + (((lane >> 2) ^ ri) << 4) + (lane & 3) * 4;
#pragma unroll
    for (int p = 1; p <= 4; p++) {
      const float4 w4 = tw[p - 1];
      const uint32_t yr = pack_bf16(fmaf(Tr[p][0], w4.x, -Ti[p][0] * w4.y), fmaf(Tr[p][1], w4.z, -Ti[p][1] * w4.w));
      const uint32_t yi = pack_bf16(fmaf(Tr[p][0], w4.y, Ti[p][0] * w4.x), fmaf(Tr[p][1], w4.w, Ti[p][1] * w4.z));
      *reinterpret_cast<uint32_t*>(t + ((p - 1) >> 1) * 8192 + ((p - 1) & 1) * 4096) = yr;
      *reinterpret_cast<uint32_t*>(t + ((p - 1) >> 1) * 8192 + ((p - 1) & 1) * 4096 + 1024) = yi;
    }
    *reinterpret_cast<uint32_t*>(t + 2 * 8192) = pack_bf16(Tr[0][0], Tr[0][1]);
    *reinterpret_cast<uint32_t*>(t + 2 * 8192 + 1024) = pack_bf16(Tr[5][0], Tr[5][1]);
  }
  if (warp == 0) CK(1, 10);
  fence_proxy_async();
  asm volatile("bar.sync 2, 512;" ::: "memory");
  if (warp == 0) CK(1, 11);
  if (wg < 3) {
    mbar_wait(bar + 8, 0);
    if (warp == 0) CK(1, 12);
    float d[64];
    const uint64_t da = make_desc_sw128(sb + K1_OFF_AT + wg * 8192, 16, 1024);
    const uint64_t db = make_desc_sw128(sb + (wg == 2 ? K1_OFF_G : K1_OFF_F), 16, 1024);
    wgmma_fence();
#pragma unroll
    for (int kk = 0; kk < 4; kk++) wgmma_ss_n128<0, 0>(d, da + kk * 2, db + kk * 2, kk != 0);
    wgmma_commit();
    wgmma_wait<0>();
    reg_fence(d);
    if (warp == 0) CK(1, 13);
    const int w = warp & 3, rh = w & 1;
    const int mid = lane >> 3, j = lane & 7;
    const uint32_t st = sb + K1_OFF_ST + rh * 16;
    if (wg < 2) {
      const int R0 = (mid & 1) * NC_ + (2 * wg + (w >> 1)) * 64 + (mid >> 1) * 8 + j;
#pragma unroll
      for (int m = 0; m < 8; m += 2) {
        uint32_t pk[4];
#pragma unroll
        for (int mm = 0; mm < 2; mm++) {
          const int M = m + mm;
          pk[2 * mm] = pack_bf16(d[4 * M] - d[4 * (8 + M) + 2], d[4 * M + 1] - d[4 * (8 + M) + 3]);
          pk[2 * mm + 1] = pack_bf16(d[4 * (8 + M)] + d[4 * M + 2], d[4 * (8 + M) + 1] + d[4 * M + 3]);
        }
        const int R = R0 + m * 8;
        stmatrix_x4_trans((st + R * 32) ^ ((R & 4) << 2), pk[0], pk[1], pk[2], pk[3]);
      }
    } else if (w < 2) {
#pragma unroll
      for (int m = 0; m < 8; m += 2) {
        const int nn = (m + (mid >> 1)) * 8 + j;
        const int R = ((mid & 1) ? 289 : 256) + nn + ((nn + (mid & 1)) > 32 ? NC_ - 32 : 0);
        stmatrix_x4_trans((st + R * 32) ^ ((R & 4) << 2), pack_bf16(d[4 * m], d[4 * m + 1]), pack_bf16(d[4 * (8 + m) + 2], d[4 * (8 + m) + 3]),
                          pack_bf16(d[4 * m + 4], d[4 * m + 5]), pack_bf16(d[4 * (8 + m) + 6], d[4 * (8 + m) + 7]));
      }
    }
    if (warp == 0) CK(1, 14);
    fence_proxy_async();
  }
  asm volatile("bar.sync 2, 512;" ::: "memory");
  if (warp == 0) CK(1, 15);
  if (tid == 0) {
    TL(1, 5);
#pragma unroll 1
    for (int i = 0; i < 3; i++) tma_store_2d(&tmX1, sb + K1_OFF_ST + i * 216 * 32, row0, i * 216);
    bulk_commit();
    bulk_wait_read0();
    TL(1, 6);
    CK(1, 16);
  }
}

constexpr int K2_OFF_F = 0, K2_OFF_X = 16384, K2_OFF_WM = 0, K2_OFF_SC = 163840, K2_OFF_BAR = K2_OFF_SC + 1280 + 1024;
constexpr int K2_SMEM = K2_OFF_BAR + 64 + 1024;

__global__ void __launch_bounds__(384, 1)
k2_kernel(const __grid_constant__ CUtensorMap tmX  ,
          const __grid_constant__ CUtensorMap tmZ  , const __grid_constant__ CUtensorMap tmWm64  ,
          const bf16* __restrict__ w1, const bf16* __restrict__ c)
{
  extern __shared__ uint8_t smem_raw[];
  uint8_t* sm = smem_raw + ((1024 - (smem_u32(smem_raw) & 1023)) & 1023);
  const uint32_t sb = smem_u32(sm);
  const int tid = threadIdx.x, wg = tid >> 7, w = (tid >> 5) & 3, lane = tid & 31;
  if (blockIdx.x >= 107) {
    const uint32_t barM = sb + K2_OFF_BAR + 32;
    const int warp = tid >> 5;
    if (tid == 0) { mbar_init(barM, 1); mbar_init(barM + 8, 1); fence_mbar_init(); }
    pdl_trigger();
    if (tid < 320) {
      const uint32_t cp = __ldg(reinterpret_cast<const uint32_t*>(c) + tid);
      const float c0 = bf_lo(cp), c1 = bf_hi(cp);
      reinterpret_cast<uint32_t*>(sm + K2_OFF_SC)[tid] = pack_bf16(__fdividef(c0, 1.f + __expf(-c0)), __fdividef(c1, 1.f + __expf(-c1)));
    }
    __syncthreads();
    const int u0 = blockIdx.x - 107, nu = u0 < 15 ? 2 : 1;
    if (tid == 0) {
#pragma unroll 1
      for (int k = 0; k < 4 * nu; k++) {
        if ((k & 3) == 0) mbar_expect_tx(barM + (k >> 2) * 8, 81920);
        tma_load_2d(sb + K2_OFF_WM + k * 20480, &tmWm64, 1280 + (u0 + (k >> 2) * 25) * 64, (k & 3) * 160, barM + (k >> 2) * 8);
      }
    }
#pragma unroll 1
    for (int uu = 0; uu < nu; uu++) {
      const int u = u0 + uu * 25;
      mbar_wait(barM + uu * 8, 0);
      if (warp < 8) {
        float d[4][4];
#pragma unroll
        for (int n = 0; n < 4; n++) { d[n][0] = d[n][1] = d[n][2] = d[n][3] = 0.f; }
        const int mid = lane >> 3, j = lane & 7, kq = warp & 3, nh = warp >> 2;
        const uint32_t* sp = reinterpret_cast<const uint32_t*>(sm + K2_OFF_SC) + kq * 80 + (lane & 3);
#pragma unroll 1
        for (int k = 0; k < 10; k++) {
          const int row = kq * 160 + k * 16 + (mid & 1) * 8 + j;
          const uint32_t ra = sb + K2_OFF_WM + uu * 81920 + row * 128;
          uint32_t b0[4], b1[4];
          ldmatrix_x4_trans(b0, ra + (((nh * 4 + (mid >> 1)) ^ j) << 4));
          ldmatrix_x4_trans(b1, ra + (((nh * 4 + 2 + (mid >> 1)) ^ j) << 4));
          const uint32_t a0 = sp[k * 8], a2 = sp[k * 8 + 4];
          mma16816(d[0], a0, a0, a2, a2, b0[0], b0[1]); mma16816(d[1], a0, a0, a2, a2, b0[2], b0[3]);
          mma16816(d[2], a0, a0, a2, a2, b1[0], b1[1]); mma16816(d[3], a0, a0, a2, a2, b1[2], b1[3]);
        }
        if (lane < 4) {
          float* red = reinterpret_cast<float*>(sm + K2_OFF_SC + 1280) + kq * 64 + nh * 32 + lane * 2;
#pragma unroll
          for (int n = 0; n < 4; n++) *reinterpret_cast<float2*>(red + n * 8) = make_float2(d[n][0], d[n][1]);
        }
      }
      __syncthreads();
      if (tid < 32) {
        const float* red = reinterpret_cast<const float*>(sm + K2_OFF_SC + 1280) + tid * 2;
        const float s0 = (red[0] + red[64]) + (red[128] + red[192]), s1 = (red[1] + red[65]) + (red[129] + red[193]);
        reinterpret_cast<uint32_t*>(g_mod)[640 + u * 32 + tid] = pack_bf16(s0, s1);
      }
      __syncthreads();
    }
    if (tid == 0) TL(2, 4);
    pdl_wait();
    if (tid == 0) TL(2, 5);
    return;
  }
  const int col = blockIdx.x * 3 + wg;
  const uint32_t bar = sb + K2_OFF_BAR + 8 * wg, barT = sb + K2_OFF_BAR + 24;
  const uint32_t xb = sb + K2_OFF_X + wg * 8192;
  if (tid == 0) {
    TL(2, 0);
    for (int k = 0; k < 4; k++) mbar_init(sb + K2_OFF_BAR + 8 * k, 1);
    fence_mbar_init();
    mbar_expect_tx(barT, 16384);
    bulk_load(sb + K2_OFF_F, T_F64, 16384, barT);
    prefetch_tmap(&tmX); prefetch_tmap(&tmZ);
  }
  pdl_trigger();
  uint32_t a1[4][4], a4[4][4];
#pragma unroll
  for (int kk = 0; kk < 4; kk++) {
    const uint4 v = __ldg(reinterpret_cast<const uint4*>(T_a1) + kk * 128 + (tid & 127));
    a1[kk][0] = v.x; a1[kk][1] = v.y; a1[kk][2] = v.z; a1[kk][3] = v.w;
    const uint4 u = __ldg(reinterpret_cast<const uint4*>(T_a4) + kk * 128 + (tid & 127));
    a4[kk][0] = u.x; a4[kk][1] = u.y; a4[kk][2] = u.z; a4[kk][3] = u.w;
  }
  if (col < 256 && (col & 63) >= 32) {
#pragma unroll
    for (int e = 0; e < 4; e++) { a1[2][e] ^= 0x80008000u; a1[3][e] ^= 0x80008000u; }
#pragma unroll
    for (int kk = 0; kk < 4; kk++) { a4[kk][1] ^= 0x80008000u; a4[kk][3] ^= 0x80008000u; }
  }
  float4 tw[8];
#pragma unroll
  for (int m = 0; m < 8; m++) tw[m] = __ldg(reinterpret_cast<const float4*>(T_tw2048) + (w * 8 + m) * 32 + lane);
  __syncthreads();
  if (tid == 0) TL(2, 1);
  pdl_wait();
  if (tid == 0) TL(2, 2);
  if (tid < 32) CK(2, 0);
  if ((tid & 127) == 0) {
    mbar_expect_tx(bar, 8192);
    tma_load_2d(xb, &tmX, 0, col * 32, bar);
    tma_load_2d(xb + 4096, &tmX, 0, (NC_ + col) * 32, bar);
  }
  uint4 wv[4];
  {
    const uint4* wp = reinterpret_cast<const uint4*>(g_Wt + (size_t)col * S_) + w * 128 + lane;
#pragma unroll
    for (int k = 0; k < 4; k++) wv[k] = __ldcg(wp + k * 32);
  }
  if (tid < 32) CK(2, 11);
  mbar_wait(barT, 0);
  if (tid < 32) CK(2, 13);
  mbar_wait(bar, 0);
  if (tid == 0) TL(2, 3);
  if (tid < 32) CK(2, 1);
  if (tid == 32) {
    const int r0 = blockIdx.x * 20, nr = (S_ - r0) < 20 ? (S_ - r0) : 20;
#pragma unroll 1
    for (int r = 0; r < nr; r += 4) prefetch_l2_bulk(w1 + (size_t)(r0 + r) * F_, 4 * F_ * 2);
  }
  __syncwarp();
  const uint64_t dX = make_desc_sw128(xb, 4096, 1024), dF = make_desc_sw128(sb + K2_OFF_F, 16, 1024);
  uint32_t af[4][4];
  {
    float d1[32];
    wgmma_fence();
#pragma unroll
    for (int kk = 0; kk < 4; kk++) wgmma_rs_n64<1>(d1, a1[kk], dX + kk * 128, kk != 0);
    wgmma_commit(); wgmma_wait<0>(); reg_fence(d1);
    if (tid < 32) CK(2, 2);
#pragma unroll
    for (int m = 0; m < 8; m++) {
      const float yr0 = fmaf(d1[4 * m], tw[m].x, -d1[4 * m + 2] * tw[m].y), yi0 = fmaf(d1[4 * m], tw[m].y, d1[4 * m + 2] * tw[m].x);
      const float yr1 = fmaf(d1[4 * m + 1], tw[m].z, -d1[4 * m + 3] * tw[m].w), yi1 = fmaf(d1[4 * m + 1], tw[m].w, d1[4 * m + 3] * tw[m].z);
      af[m >> 1][(m & 1) * 2] = pack_bf16(yr0, yr1); af[m >> 1][(m & 1) * 2 + 1] = pack_bf16(yi0, yi1);
    }
  }
  float d[64];
  if (tid < 32) CK(2, 3);
  wgmma_fence();
#pragma unroll
  for (int kk = 0; kk < 4; kk++) wgmma_rs_n128<0>(d, af[kk], dF + kk * 2, kk != 0);
  wgmma_commit(); wgmma_wait<0>(); reg_fence(d);
  if (tid < 32) CK(2, 4);
  {
    const uint32_t wq[16] = {wv[0].x, wv[0].y, wv[0].z, wv[0].w, wv[1].x, wv[1].y, wv[1].z, wv[1].w, wv[2].x, wv[2].y, wv[2].z, wv[2].w, wv[3].x, wv[3].y, wv[3].z, wv[3].w};
#pragma unroll
    for (int m = 0; m < 8; m++) {
      float yr[2], yi[2];
#pragma unroll
      for (int e = 0; e < 2; e++) {
        const float orr = d[4 * m + e] - d[4 * (8 + m) + 2 + e];
        const float oi = d[4 * (8 + m) + e] + d[4 * m + 2 + e];
        const float a = bf_lo(wq[2 * m + e]), b = bf_hi(wq[2 * m + e]);
        yr[e] = fmaf(orr, a, -oi * b); yi[e] = fmaf(orr, b, oi * a);
      }
      af[m >> 1][(m & 1) * 2] = pack_bf16(yr[0], yr[1]); af[m >> 1][(m & 1) * 2 + 1] = pack_bf16(yi[0], yi[1]);
    }
  }
  if (tid < 32) CK(2, 5);
  wgmma_fence();
#pragma unroll
  for (int kk = 0; kk < 4; kk++) wgmma_rs_n128<0>(d, af[kk], dF + kk * 2, kk != 0);
  wgmma_commit(); wgmma_wait<0>(); reg_fence(d);
  if (tid < 32) CK(2, 6);
  const int mid = lane >> 3, j = lane & 7;
  const int krow = (mid & 1) * 32 + 8 * w + j;
  const uint32_t strow = xb + krow * 128 + (((mid >> 1) ^ j) << 4);
  {
#pragma unroll
    for (int m = 0; m < 8; m += 2) {
      uint32_t pk[4];
#pragma unroll
      for (int mm = 0; mm < 2; mm++) {
        const int M = m + mm;
        const float r0 = d[4 * M] + d[4 * (8 + M) + 2], i0 = d[4 * M + 2] - d[4 * (8 + M)];
        const float r1 = d[4 * M + 1] + d[4 * (8 + M) + 3], i1 = d[4 * M + 3] - d[4 * (8 + M) + 1];
        pk[2 * mm] = pack_bf16(fmaf(r0, tw[M].x, i0 * tw[M].y), fmaf(r1, tw[M].z, i1 * tw[M].w));
        pk[2 * mm + 1] = pack_bf16(fmaf(i0, tw[M].x, -r0 * tw[M].y), fmaf(i1, tw[M].z, -r1 * tw[M].w));
      }
      stmatrix_x4(strow ^ (m << 4), pk[0], pk[1], pk[2], pk[3]);
    }
  }
  fence_proxy_async();
  asm volatile("bar.sync %0, 128;" ::"r"(1 + wg) : "memory");
  float d4[32];
  if (tid < 32) CK(2, 7);
  wgmma_fence();
#pragma unroll
  for (int kk = 0; kk < 4; kk++) wgmma_rs_n64<1>(d4, a4[kk], dX + kk * 128, kk != 0);
  wgmma_commit(); wgmma_wait<0>(); reg_fence(d4);
  if (tid < 32) CK(2, 8);
  asm volatile("bar.sync %0, 128;" ::"r"(1 + wg) : "memory");
#pragma unroll
  for (int m = 0; m < 8; m += 2)
    stmatrix_x4(strow ^ (m << 4), pack_bf16(d4[4 * m], d4[4 * m + 1]), pack_bf16(d4[4 * m + 2], d4[4 * m + 3]),
                pack_bf16(d4[4 * m + 4], d4[4 * m + 5]), pack_bf16(d4[4 * m + 6], d4[4 * m + 7]));
  fence_proxy_async();
  asm volatile("bar.sync %0, 128;" ::"r"(1 + wg) : "memory");
  if (tid < 32) CK(2, 9);
  if ((tid & 127) == 0) {
    tma_store_2d(&tmZ, xb, 0, col * 32);
    tma_store_2d(&tmZ, xb + 4096, 0, (NC_ + col) * 32);
    bulk_commit();
    bulk_wait_read0();
    if (tid == 0) { TL(2, 6); CK(2, 10); }
  }
}

constexpr int K3_VP = 72;
constexpr int K3_OFF_F = 0, K3_OFF_G = 16384, K3_OFF_Z = 32768, K3_OFF_V = K3_OFF_Z + 20736, K3_OFF_MOD = K3_OFF_V + 160 * K3_VP * 4, K3_OFF_PART = K3_OFF_MOD + 3840, K3_OFF_BAR = K3_OFF_PART + 512;
constexpr int K3_SMEM = K3_OFF_BAR + 64 + 1024;

__global__ void __launch_bounds__(512, 1)
k3_kernel(const __grid_constant__ CUtensorMap tmZ  , const bf16* __restrict__ x, const bf16* __restrict__ w2)
{
  extern __shared__ uint8_t smem_raw[];
  uint8_t* sm = smem_raw + ((1024 - (smem_u32(smem_raw) & 1023)) & 1023);
  const uint32_t sb = smem_u32(sm);
  const int tid = threadIdx.x, wg = tid >> 7, warp = tid >> 5, w = warp & 3, lane = tid & 31;
  const int i = lane >> 2, c = lane & 3;
  const int row0 = blockIdx.x * 16;
  const uint32_t bar = sb + K3_OFF_BAR, barT = bar + 8;
  float* V = reinterpret_cast<float*>(sm + K3_OFF_V);
  if (tid == 0) {
    TL(3, 0);
    mbar_init(bar, 1); mbar_init(barT, 1); fence_mbar_init();
    mbar_expect_tx(barT, 32768);
    bulk_load(sb + K3_OFF_F, T_F64, 16384, barT);
    bulk_load(sb + K3_OFF_G, T_Gi, 16384, barT);
    prefetch_tmap(&tmZ);
  }
  pdl_trigger();
  const int p = 1 + 2 * (wg & 1) + (w >> 1);
  float4 tw[8];
#pragma unroll
  for (int m = 0; m < 8; m++) tw[m] = __ldg(reinterpret_cast<const float4*>(T_tw640i) + (p - 1) * 32 + 4 * m + c);
  uint32_t P[10];
  {
    const uint32_t* xp = reinterpret_cast<const uint32_t*>(x + (size_t)(row0 + warp) * D_) + lane;
#pragma unroll
    for (int a = 0; a < 10; a++) P[a] = __ldg(xp + a * 32);
  }
  __syncthreads();
  if (tid == 0) TL(3, 1);
  pdl_wait();
  if (tid == 0) {
    TL(3, 2);
    CK(3, 0);
    mbar_expect_tx(bar, 648 * 32 + 3840);
#pragma unroll 1
    for (int k = 0; k < 3; k++) tma_load_2d(sb + K3_OFF_Z + k * 216 * 32, &tmZ, row0, k * 216, bar);
    bulk_load(sb + K3_OFF_MOD, g_mod + 1280, 3840, bar);
  }
  mbar_wait(bar, 0);
  if (tid == 0) TL(3, 3);
  if (tid < 32) CK(3, 1);
  if (tid == 12 * 32) {
    const char* base = reinterpret_cast<const char*>(w2) + (size_t)blockIdx.x * 55296;
#pragma unroll 1
    for (int k = 0; k < 4; k++) prefetch_l2_bulk(base + k * 13824, 13824);
  }
  __syncwarp();
  if (wg < 3) {
    mbar_wait(barT, 0);
    const int rh = w & 1;
    const int mid = lane >> 3, j = lane & 7;
    uint32_t af[4][4];
#pragma unroll
    for (int kk = 0; kk < 4; kk++) {
      const int q = 16 * kk + (mid >> 1) * 8 + j;
      int R;
      if (wg < 2) R = (mid & 1) * NC_ + (p - 1) * 64 + q;
      else R = ((mid & 1) ? 289 : 256) + q + ((q + (mid & 1)) > 32 ? NC_ - 32 : 0);
      ldmatrix_x4_trans(af[kk], (sb + K3_OFF_Z + rh * 16 + R * 32) ^ ((R & 4) << 2));
    }
    float d[64];
    const uint64_t dF = make_desc_sw128(sb + (wg == 2 ? K3_OFF_G : K3_OFF_F), 16, 1024);
    wgmma_fence();
#pragma unroll
    for (int kk = 0; kk < 4; kk++) wgmma_rs_n128<0>(d, af[kk], dF + kk * 2, kk != 0);
    wgmma_commit(); wgmma_wait<0>(); reg_fence(d);
    if (tid < 32) CK(3, 2);
    const int rr = 8 * rh + i;
    if (wg < 2) {
      float* v0 = V + ((2 * p) * 16 + rr) * K3_VP + 2 * c;
#pragma unroll
      for (int m = 0; m < 8; m++) {
        const float r0 = d[4 * m] + d[4 * (8 + m) + 2], i0 = d[4 * m + 2] - d[4 * (8 + m)];
        const float r1 = d[4 * m + 1] + d[4 * (8 + m) + 3], i1 = d[4 * m + 3] - d[4 * (8 + m) + 1];
        *reinterpret_cast<float2*>(v0 + 8 * m) = make_float2(fmaf(r0, tw[m].x, -i0 * tw[m].y), fmaf(r1, tw[m].z, -i1 * tw[m].w));
        *reinterpret_cast<float2*>(v0 + 16 * K3_VP + 8 * m) = make_float2(fmaf(i0, tw[m].x, r0 * tw[m].y), fmaf(i1, tw[m].z, r1 * tw[m].w));
      }
    } else if (w < 2) {
      float* v0 = V + rr * K3_VP + 2 * c;
#pragma unroll
      for (int m = 0; m < 8; m++) {
        *reinterpret_cast<float2*>(v0 + 8 * m) = make_float2(d[4 * m], d[4 * m + 1]);
        *reinterpret_cast<float2*>(v0 + 16 * K3_VP + 8 * m) = make_float2(d[4 * (8 + m) + 2], d[4 * (8 + m) + 3]);
      }
    }
  }
  __syncthreads();
  if (tid == 0) TL(3, 4);
  if (tid < 32) CK(3, 3);
  {
    const uint32_t* modp = reinterpret_cast<const uint32_t*>(sm + K3_OFF_MOD) + lane;
    float2 t[10];
#pragma unroll
    for (int k = 0; k < 10; k++) t[k] = *reinterpret_cast<const float2*>(V + (k * 16 + warp) * K3_VP + 2 * lane);
    float y[10][2];
#pragma unroll
    for (int j = 0; j < 2; j++) {
      const float v0 = j ? t[0].y : t[0].x, v5 = j ? t[1].y : t[1].x;
      const float r1 = j ? t[2].y : t[2].x, i1 = j ? t[3].y : t[3].x, r2 = j ? t[4].y : t[4].x, i2 = j ? t[5].y : t[5].x;
      const float r3 = j ? t[6].y : t[6].x, i3 = j ? t[7].y : t[7].x, r4 = j ? t[8].y : t[8].x, i4 = j ? t[9].y : t[9].x;
      float E[5], O[5];
      {
        const float A1 = fmaf(2.f * C2_, r4, fmaf(2.f * C1_, r2, v0)), B1 = fmaf(2.f * S2_, i4, 2.f * S1_ * i2);
        const float A2 = fmaf(2.f * C1_, r4, fmaf(2.f * C2_, r2, v0)), B2 = fmaf(-2.f * S1_, i4, 2.f * S2_ * i2);
        E[0] = fmaf(2.f, r2 + r4, v0);
        E[1] = A1 - B1; E[4] = A1 + B1; E[2] = A2 - B2; E[3] = A2 + B2;
      }
      {
        const float A1 = fmaf(2.f * C2_, r1, fmaf(2.f * C1_, r3, v5)), B1 = fmaf(2.f * S2_, i1, 2.f * S1_ * i3);
        const float A2 = fmaf(2.f * C1_, r1, fmaf(2.f * C2_, r3, v5)), B2 = fmaf(-2.f * S1_, i1, 2.f * S2_ * i3);
        O[0] = fmaf(2.f, r3 + r1, v5);
        O[1] = A1 + B1; O[4] = A1 - B1; O[2] = A2 + B2; O[3] = A2 - B2;
      }
#pragma unroll
      for (int a = 0; a < 10; a++) y[a][j] = (a & 1) ? E[a % 5] - O[a % 5] : E[a % 5] + O[a % 5];
    }
    uint32_t* xo = reinterpret_cast<uint32_t*>(g_x2 + (size_t)(row0 + warp) * D_) + lane;
#pragma unroll
    for (int a = 0; a < 10; a++) {
      P[a] = badd2(P[a], bmul2(modp[a * 32], pack_bf16(y[a][0], y[a][1])));
      xo[a * 32] = P[a];
    }
    if (tid < 32) CK(3, 4);
#pragma unroll 1
    for (int it = 0; it < 2; it++) {
      layernorm_warp(P, lane);
      if (tid < 32) CK(3, 6 + 2 * it);
      if (it == 0) {
#pragma unroll
        for (int a = 0; a < 10; a++) P[a] = badd2(bmul2(P[a], badd2(BF_ONE2, modp[640 + a * 32])), modp[320 + a * 32]);
      }
    }
    uint32_t* ho = reinterpret_cast<uint32_t*>(g_h3 + (size_t)(row0 + warp) * D_) + lane;
#pragma unroll
    for (int a = 0; a < 10; a++) ho[a * 32] = P[a];
  }
  if (tid == 0) { TL(3, 6); CK(3, 9); }
}

#include <initializer_list>
#include <cstdio>

typedef CUresult (*EncFn)(CUtensorMap*, CUtensorMapDataType, cuuint32_t, void*, const cuuint64_t*, const cuuint64_t*, const cuuint32_t*, const cuuint32_t*, CUtensorMapInterleave, CUtensorMapSwizzle, CUtensorMapL2promotion, CUtensorMapFloatOOBfill);
static EncFn g_enc;
static CUtensorMap mk(void* base, int rank, std::initializer_list<cuuint64_t> dims, std::initializer_list<cuuint64_t> strides, std::initializer_list<cuuint32_t> box, CUtensorMapSwizzle sw, CUtensorMapDataType dt = CU_TENSOR_MAP_DATA_TYPE_BFLOAT16) {
  CUtensorMap m; cuuint32_t es[5] = {1, 1, 1, 1, 1};
  cuuint64_t d[5], s[5]; cuuint32_t b[5];
  int i = 0; for (auto v : dims) d[i++] = v; i = 0; for (auto v : strides) s[i++] = v; i = 0; for (auto v : box) b[i++] = v;
  CUresult r = g_enc(&m, dt, rank, base, d, s, b, es, CU_TENSOR_MAP_INTERLEAVE_NONE, sw, CU_TENSOR_MAP_L2_PROMOTION_L2_128B, CU_TENSOR_MAP_FLOAT_OOB_FILL_NONE);
  if (r != CUDA_SUCCESS) { fprintf(stderr, "tensor map encode failed %d\n", (int)r); }
  return m;
}
constexpr int G1 = 4, ST1 = 4, G2 = 1, ST2 = 4;
template<typename... Args>
static void launch(void (*kern)(Args...), int grid, int block, int smem, int cluster, bool pdl, cudaStream_t st, Args... args) {
  cudaLaunchConfig_t cfg = {}; cfg.gridDim = dim3(grid); cfg.blockDim = dim3(block); cfg.dynamicSmemBytes = smem; cfg.stream = st;
  cudaLaunchAttribute at[2]; int n = 0;
  if (cluster > 1) { at[n].id = cudaLaunchAttributeClusterDimension; at[n].val.clusterDim.x = cluster; at[n].val.clusterDim.y = 1; at[n].val.clusterDim.z = 1; n++; }
  if (pdl) { at[n].id = cudaLaunchAttributeProgrammaticStreamSerialization; at[n].val.programmaticStreamSerializationAllowed = 1; n++; }
  cfg.attrs = at; cfg.numAttrs = n;
  cudaError_t e = cudaLaunchKernelEx(&cfg, kern, args...);
  if (e != cudaSuccess) fprintf(stderr, "launch failed: %s\n", cudaGetErrorString(e));
}
static int g_nk = 6; static int g_pdl = 1;
extern "C" void kernel_launch(void* const* d_in, const int* in_sizes, int n_in, void* d_out, int out_size) {
  const bf16* x = (const bf16*)d_in[0]; const bf16* wr = (const bf16*)d_in[1]; const bf16* wi = (const bf16*)d_in[2];
  const bf16* w1 = (const bf16*)d_in[4]; const bf16* b1 = (const bf16*)d_in[5]; const bf16* w2 = (const bf16*)d_in[6]; const bf16* b2 = (const bf16*)d_in[7];
  const bf16* c = (const bf16*)d_in[8]; const bf16* w_mod = (const bf16*)d_in[9];
  static bool init = false;
  static CUtensorMap tmWm64, tmWr, tmWi, tX2, tmWt, tmX1s, tmX1l, tmZs, tmZl, tA1, tB1, tO1, tA2, tB2, tO2;
  static void *pX1, *pZ, *pH3, *pU, *pX2, *pMod;
  static void* last_out = nullptr; static const void* last_w1 = nullptr; static const void* last_w2 = nullptr; static const void* last_wm = nullptr; static const void* last_wr = nullptr; static const void* last_wi = nullptr;
  if (!init) {
    void* fn; cudaDriverEntryPointQueryResult qr;
    cudaGetDriverEntryPoint("cuTensorMapEncodeTiled", &fn, cudaEnableDefault, &qr); g_enc = (EncFn)fn;
    cudaGetSymbolAddress(&pX1, g_X1); cudaGetSymbolAddress(&pZ, g_Z); cudaGetSymbolAddress(&pH3, g_h3); cudaGetSymbolAddress(&pU, g_u); cudaGetSymbolAddress(&pX2, g_x2); cudaGetSymbolAddress(&pMod, g_mod);
    tmX1s = mk(pX1, 2, {2048, 642}, {4096}, {16, 216}, CU_TENSOR_MAP_SWIZZLE_32B);
    { void* pWt; cudaGetSymbolAddress(&pWt, g_Wt); tmWt = mk(pWt, 2, {2048, 321}, {8192}, {16, 168}, CU_TENSOR_MAP_SWIZZLE_64B, CU_TENSOR_MAP_DATA_TYPE_UINT32); }
    tmZl = mk(pZ, 2, {2048, 642}, {4096}, {16, 216}, CU_TENSOR_MAP_SWIZZLE_32B);
    tmX1l = mk(pX1, 2, {64, 642 * 32}, {128}, {64, 32}, CU_TENSOR_MAP_SWIZZLE_128B);
    tmZs = mk(pZ, 2, {64, 642 * 32}, {128}, {64, 32}, CU_TENSOR_MAP_SWIZZLE_128B);
    tA1 = mk(pH3, 2, {640, 2048}, {1280}, {64, G1 == 1 ? 64 : 128 / G1}, CU_TENSOR_MAP_SWIZZLE_128B);
    tX2 = mk(pX2, 2, {640, 2048}, {1280}, {80, 128}, CU_TENSOR_MAP_SWIZZLE_NONE);
    tO1 = mk(pU, 2, {1728, 640}, {3456}, {72, 128}, CU_TENSOR_MAP_SWIZZLE_NONE);
    tB2 = mk(pU, 2, {1728, 640}, {3456}, {64, 160 / G2}, CU_TENSOR_MAP_SWIZZLE_128B);
    cudaFuncSetAttribute(k0_kernel, cudaFuncAttributePreferredSharedMemoryCarveout, 100);
    cudaFuncSetAttribute(k1_kernel, cudaFuncAttributeMaxDynamicSharedMemorySize, K1_SMEM);
    cudaFuncSetAttribute(k2_kernel, cudaFuncAttributeMaxDynamicSharedMemorySize, K2_SMEM);
    cudaFuncSetAttribute(k3_kernel, cudaFuncAttributeMaxDynamicSharedMemorySize, K3_SMEM);
    cudaFuncSetAttribute(gemm_kernel<1, G1, ST1>, cudaFuncAttributeMaxDynamicSharedMemorySize, GemmSmem<1, G1, ST1>::TOTAL);
    cudaFuncSetAttribute(gemm_kernel<2, G2, ST2>, cudaFuncAttributeMaxDynamicSharedMemorySize, GemmSmem<2, G2, ST2>::TOTAL);
    init = true;
  }
  if (last_out != d_out || last_w1 != w1 || last_w2 != w2 || last_wm != w_mod || last_wr != wr || last_wi != wi) {
    last_wm = w_mod; last_wr = wr; last_wi = wi;
    tmWm64 = mk((void*)w_mod, 2, {3840, 640}, {7680}, {64, 160}, CU_TENSOR_MAP_SWIZZLE_128B);
    tmWr = mk((void*)wr, 2, {10272, 64}, {20544}, {168, 16}, CU_TENSOR_MAP_SWIZZLE_NONE);
    tmWi = mk((void*)wi, 2, {10272, 64}, {20544}, {168, 16}, CU_TENSOR_MAP_SWIZZLE_NONE);
    tB1 = mk((void*)w1, 3, {144, 12, 2048}, {288, 3456}, {64, 1, 64}, CU_TENSOR_MAP_SWIZZLE_128B);
    tA2 = mk((void*)w2, 3, {64, 1728, 32}, {4096, 128}, {64, 64, 2}, CU_TENSOR_MAP_SWIZZLE_128B);
    tO2 = mk(d_out, 2, {640, 2048}, {1280}, {80, 128}, CU_TENSOR_MAP_SWIZZLE_NONE);
    last_out = d_out; last_w1 = w1; last_w2 = w2;
  }
  cudaStream_t st = cudaStreamPerThread;
  const bool pdl = g_pdl;
  if (g_nk > 0) launch(k0_kernel, 80, 128, K0_SMEM, 1, false, st, tmWm64, c);
  if (g_nk > 1) launch(k1_kernel, 128, 640, K1_SMEM, 1, pdl, st, tmX1s, tmWm64, tmWt, tmWr, tmWi, x, c, w_mod, wr, wi);
  if (g_nk > 2) launch(k2_kernel, 132, 384, K2_SMEM, 1, pdl, st, tmX1l, tmZs, tmWm64, w1, c);
  if (g_nk > 3) launch(k3_kernel, 128, 512, K3_SMEM, 1, pdl, st, tmZl, x, w2);
  if (g_nk > 4) launch(gemm_kernel<1, G1, ST1>, 120, 512, GemmSmem<1, G1, ST1>::TOTAL, 2 * G1, pdl, st, tA1, tB1, tO1, tO1, b1, (const bf16*)nullptr, (const bf16*)nullptr, (bf16*)w2);
  if (g_nk > 5) launch(gemm_kernel<2, G2, ST2>, 128, 512, GemmSmem<2, G2, ST2>::TOTAL, 2 * G2, pdl, st, tA2, tB2, tO2, tX2, b2, (const bf16*)pX2, (const bf16*)pMod + 5 * 640, (bf16*)d_out);
}
```
